```python
import torch

def _softmax(x, axis=-1):
    return torch.softmax(x, dim=axis)
def _gelu(x):
    return torch.nn.functional.gelu(x, approximate="tanh")
def _silu(x):
    return torch.nn.functional.silu(x)
def _sigmoid(x):
    return torch.sigmoid(x)
def _layernorm(x, axis=-1, eps=1e-5):
    m = x.mean(dim=axis, keepdim=True)
    v = x.var(dim=axis, keepdim=True, unbiased=False)
    return (x - m) / torch.sqrt(v + eps)
def _scatter_add(tgt, idx, src, axis=0):
    return tgt.clone().index_add_(axis, idx, src)
def _segment_sum(src, seg, n):
    out = torch.zeros((n,) + src.shape[1:], dtype=src.dtype)
    return out.index_add_(0, seg, src)
def _pad(x, pw):
    flat = tuple(v for pair in reversed(pw) for v in pair)
    return torch.nn.functional.pad(x, flat)

kernel_name = 'sequential_preLN__linear_attn_block__glu_gated_bilinear__prompt'

def setup_inputs():

    _w = (lambda a: (lambda t: t.to(torch.bfloat16) if t.is_floating_point() else t)(torch.as_tensor(a)))
    def _A_setup():
        B, S, D = 1, 2048, 512
        return {
            "x": _w((lambda *s: torch.randn(*s, dtype=torch.bfloat16) * 0.05)(B, S, D)),
            "wqkv": _w((lambda *s: torch.randn(*s, dtype=torch.bfloat16) * 0.05)(D, 3 * D)),
            "wo": _w((lambda *s: torch.randn(*s, dtype=torch.bfloat16) * 0.05)(D, D)),
        }
    _A_in = _A_setup()

    def _B_setup():
        B, S, D, F = 1, 2048, 512, 1376
        return {
            "x": _w((lambda *s: torch.randn(*s, dtype=torch.bfloat16) * 0.05)(B, S, D)),
            "w_gate": _w((lambda *s: torch.randn(*s, dtype=torch.bfloat16) * 0.2)(D, F) * (D ** -0.5)),
            "w_up": _w((lambda *s: torch.randn(*s, dtype=torch.bfloat16) * 0.2)(D, F) * (D ** -0.5)),
            "w_down": _w((lambda *s: torch.randn(*s, dtype=torch.bfloat16) * 0.2)(F, D) * (F ** -0.5)),
        }
    _B_in = _B_setup()

    return {
        "A_x": _A_in["x"],
        "A_wqkv": _A_in["wqkv"],
        "A_wo": _A_in["wo"],
        "B_x": _B_in["x"],
        "B_w_gate": _B_in["w_gate"],
        "B_w_up": _B_in["w_up"],
        "B_w_down": _B_in["w_down"],
    }

def reference(A_x, A_wqkv, A_wo, B_x, B_w_gate, B_w_up, B_w_down):
    def _A_ref(x, wqkv, wo):
        B, S, D = x.shape
        H = 32; Dh = D // H
        qkv = (lambda x, *d: x.permute(*d))((x @ wqkv).reshape(B, S, 3, H, Dh), 2, 0, 3, 1, 4)
        q, k, v = qkv[0], qkv[1], qkv[2]
        phi = lambda t: torch.where(t > 0, t + 1, torch.exp(t)) + 1e-6
        pq, pk = phi(q), phi(k)
        kv = torch.einsum("bhsd,bhse->bhde", pk, v)
        z = torch.einsum("bhsd->bhd", pk)
        num = torch.einsum("bhqd,bhde->bhqe", pq, kv)
        den = torch.einsum("bhqd,bhd->bhq", pq, z)[..., None] + 1e-6
        o = num / den
        return (lambda x, *d: x.permute(*d))(o, 0, 2, 1, 3).reshape(B, S, D) @ wo

    def _B_ref(x, w_gate, w_up, w_down):
        g = torch.einsum("bsd,df->bsf", x, w_gate)
        u = torch.einsum("bsd,df->bsf", x, w_up)
        h = g * u
        return torch.einsum("bsf,fd->bsd", h, w_down)

    x = A_x
    h = x + _A_ref(_layernorm(x, axis=-1), A_wqkv, A_wo)
    h2 = h + _B_ref(_layernorm(h, axis=-1), B_w_gate, B_w_up, B_w_down)
    return h2
```

```cpp
#include <cuda_runtime.h>
#include <cuda_bf16.h>
#include <cuda.h>
#include <stdint.h>

namespace {

constexpr int DM = 512;
constexpr int FF = 1376;
constexpr int NCTA = 128;
constexpr int NSLOT = 24;
constexpr int TILE_BYTES = 8192;
constexpr int Q_KV = 0, Q_Q = 16, Q_WO = 24, Q_VIRT = 40, Q_GU = 42, Q_DN = 90, NTILES = 134;

constexpr int SM_STAGE = NSLOT * TILE_BYTES;
constexpr int SM_BAR = SM_STAGE + 32768;
constexpr int SM_EBAR = SM_BAR + 2 * NSLOT * 8;
constexpr int SM_MISC = SM_EBAR + 8;
constexpr int SM_TOTAL = SM_MISC + 64;

constexpr int SPIN_LIMIT = 1 << 18;
constexpr uint32_t POISON = 0xFFFFFFFFu;

__device__ uint4 g_o[128 * 32 * 32];
__device__ uint4 g_h[128 * 32 * 32];
__device__ uint4 g_hh[128 * 88 * 32];
__device__ uint4 g_hstat[2048 * 4];
__device__ float4 g_kv[2][32 * 32 * 2];
__device__ float4 g_z[2][32 * 4];
__device__ uint4 g_wgu[8 * 8 * 6 * 512];
__device__ uint32_t g_kvcnt[8 * 32];
__device__ uint32_t g_repack_cnt;
__device__ uint32_t g_epoch;
#define TSTAMP(k) do {} while (0)

__device__ __forceinline__ uint32_t smem_u32(const void* p) { return (uint32_t)__cvta_generic_to_shared(p); }
__device__ __forceinline__ void mbar_init(uint32_t bar, uint32_t cnt) {
  asm volatile("mbarrier.init.shared::cta.b64 [%0], %1;" ::"r"(bar), "r"(cnt) : "memory");
}
__device__ __forceinline__ void mbar_expect_tx(uint32_t bar, uint32_t bytes) {
  asm volatile("mbarrier.arrive.expect_tx.shared::cta.b64 _, [%0], %1;" ::"r"(bar), "r"(bytes) : "memory");
}
__device__ __forceinline__ void mbar_arrive(uint32_t bar) {
  asm volatile("mbarrier.arrive.shared::cta.b64 _, [%0];" ::"r"(bar) : "memory");
}
__device__ __forceinline__ void mbar_wait(uint32_t bar, uint32_t parity) {
  asm volatile(
      "{\n.reg .pred p;\n.reg .u32 c;\nmov.u32 c, 0;\n"
      "W%=:\nmbarrier.try_wait.parity.shared::cta.b64 p, [%0], %1;\n@p bra D%=;\n"
      "add.u32 c, c, 1;\nsetp.lt.u32 p, c, %2;\n@p bra W%=;\nD%=:\n}\n" ::"r"(bar), "r"(parity), "n"(SPIN_LIMIT)
      : "memory");
}
__device__ __forceinline__ void tma_2d_mc(uint32_t dst, const CUtensorMap* tm, uint32_t bar, int c0, int c1) {
  asm volatile(
      "cp.async.bulk.tensor.2d.shared::cluster.global.mbarrier::complete_tx::bytes.multicast::cluster [%0], [%1, {%3, %4}], [%2], %5;" ::"r"(dst),
      "l"((uint64_t)tm), "r"(bar), "r"(c0), "r"(c1), "h"((uint16_t)3)
      : "memory");
}
__device__ __forceinline__ void tma_5d_mc(uint32_t dst, const CUtensorMap* tm, uint32_t bar, int c0, int c4) {
  asm volatile(
      "cp.async.bulk.tensor.5d.shared::cluster.global.mbarrier::complete_tx::bytes.multicast::cluster [%0], [%1, {%3, %4, %4, %4, %5}], [%2], %6;" ::"r"(dst),
      "l"((uint64_t)tm), "r"(bar), "r"(c0), "r"(0), "r"(c4), "h"((uint16_t)3)
      : "memory");
}
__device__ __forceinline__ void bulk_g2s_mc(uint32_t dst, const void* src, uint32_t bytes, uint32_t bar) {
  asm volatile("cp.async.bulk.shared::cluster.global.mbarrier::complete_tx::bytes.multicast::cluster [%0], [%1], %2, [%3], %4;" ::"r"(dst),
               "l"(src), "r"(bytes), "r"(bar), "h"((uint16_t)3)
               : "memory");
}
__device__ __forceinline__ void mbar_arrive_cluster(uint32_t bar, uint32_t rank, uint32_t count) {
  asm volatile(
      "{\n.reg .b32 ra;\nmapa.shared::cluster.u32 ra, %0, %1;\nmbarrier.arrive.shared::cluster.b64 _, [ra], %2;\n}\n" ::"r"(bar), "r"(rank), "r"(count)
      : "memory");
}
__device__ __forceinline__ void wgmma_fence() { asm volatile("wgmma.fence.sync.aligned;" ::: "memory"); }
__device__ __forceinline__ void wgmma_commit() { asm volatile("wgmma.commit_group.sync.aligned;" ::: "memory"); }
template <int N>
__device__ __forceinline__ void wgmma_wait() { asm volatile("wgmma.wait_group.sync.aligned %0;" ::"n"(N) : "memory"); }

__device__ __forceinline__ uint64_t make_desc(uint32_t lo) {
  return (uint64_t)lo | ((uint64_t)((1024u >> 4) | (1u << 30)) << 32);
}

__device__ __forceinline__ void wgmma_rs_n64(float (&d)[32], uint32_t a0, uint32_t a1, uint32_t a2, uint32_t a3, uint64_t descB, int scaleD) {
  asm volatile(
    "{\n.reg .pred p;\nsetp.ne.b32 p, %37, 0;\n"
    "wgmma.mma_async.sync.aligned.m64n64k16.f32.bf16.bf16 "
    "{%0, %1, %2, %3, %4, %5, %6, %7, %8, %9, %10, %11, %12, %13, %14, %15, "
    "%16, %17, %18, %19, %20, %21, %22, %23, %24, %25, %26, %27, %28, %29, %30, %31}, "
    "{%32, %33, %34, %35}, %36, p, 1, 1, 1;\n}\n"
    : "+f"(d[0]), "+f"(d[1]), "+f"(d[2]), "+f"(d[3]), "+f"(d[4]), "+f"(d[5]), "+f"(d[6]), "+f"(d[7]),
      "+f"(d[8]), "+f"(d[9]), "+f"(d[10]), "+f"(d[11]), "+f"(d[12]), "+f"(d[13]), "+f"(d[14]), "+f"(d[15]),
      "+f"(d[16]), "+f"(d[17]), "+f"(d[18]), "+f"(d[19]), "+f"(d[20]), "+f"(d[21]), "+f"(d[22]), "+f"(d[23]),
      "+f"(d[24]), "+f"(d[25]), "+f"(d[26]), "+f"(d[27]), "+f"(d[28]), "+f"(d[29]), "+f"(d[30]), "+f"(d[31])
    : "r"(a0), "r"(a1), "r"(a2), "r"(a3), "l"(descB), "r"(scaleD));
}

__device__ __forceinline__ void wgmma_rs_n128(float (&d)[64], uint32_t a0, uint32_t a1, uint32_t a2, uint32_t a3, uint64_t descB, int scaleD) {
  asm volatile(
    "{\n.reg .pred p;\nsetp.ne.b32 p, %69, 0;\n"
    "wgmma.mma_async.sync.aligned.m64n128k16.f32.bf16.bf16 "
    "{%0, %1, %2, %3, %4, %5, %6, %7, %8, %9, %10, %11, %12, %13, %14, %15, "
    "%16, %17, %18, %19, %20, %21, %22, %23, %24, %25, %26, %27, %28, %29, %30, %31, "
    "%32, %33, %34, %35, %36, %37, %38, %39, %40, %41, %42, %43, %44, %45, %46, %47, "
    "%48, %49, %50, %51, %52, %53, %54, %55, %56, %57, %58, %59, %60, %61, %62, %63}, "
    "{%64, %65, %66, %67}, %68, p, 1, 1, 1;\n}\n"
    : "+f"(d[0]), "+f"(d[1]), "+f"(d[2]), "+f"(d[3]), "+f"(d[4]), "+f"(d[5]), "+f"(d[6]), "+f"(d[7]),
      "+f"(d[8]), "+f"(d[9]), "+f"(d[10]), "+f"(d[11]), "+f"(d[12]), "+f"(d[13]), "+f"(d[14]), "+f"(d[15]),
      "+f"(d[16]), "+f"(d[17]), "+f"(d[18]), "+f"(d[19]), "+f"(d[20]), "+f"(d[21]), "+f"(d[22]), "+f"(d[23]),
      "+f"(d[24]), "+f"(d[25]), "+f"(d[26]), "+f"(d[27]), "+f"(d[28]), "+f"(d[29]), "+f"(d[30]), "+f"(d[31]),
      "+f"(d[32]), "+f"(d[33]), "+f"(d[34]), "+f"(d[35]), "+f"(d[36]), "+f"(d[37]), "+f"(d[38]), "+f"(d[39]),
      "+f"(d[40]), "+f"(d[41]), "+f"(d[42]), "+f"(d[43]), "+f"(d[44]), "+f"(d[45]), "+f"(d[46]), "+f"(d[47]),
      "+f"(d[48]), "+f"(d[49]), "+f"(d[50]), "+f"(d[51]), "+f"(d[52]), "+f"(d[53]), "+f"(d[54]), "+f"(d[55]),
      "+f"(d[56]), "+f"(d[57]), "+f"(d[58]), "+f"(d[59]), "+f"(d[60]), "+f"(d[61]), "+f"(d[62]), "+f"(d[63])
    : "r"(a0), "r"(a1), "r"(a2), "r"(a3), "l"(descB), "r"(scaleD));
}

__device__ __forceinline__ void wgmma_rs_n176(float (&d)[88], uint32_t a0, uint32_t a1, uint32_t a2, uint32_t a3, uint64_t descB, int scaleD) {
  asm volatile(
    "{\n.reg .pred p;\nsetp.ne.b32 p, %93, 0;\n"
    "wgmma.mma_async.sync.aligned.m64n176k16.f32.bf16.bf16 "
    "{%0, %1, %2, %3, %4, %5, %6, %7, %8, %9, %10, %11, %12, %13, %14, %15, "
    "%16, %17, %18, %19, %20, %21, %22, %23, %24, %25, %26, %27, %28, %29, %30, %31, "
    "%32, %33, %34, %35, %36, %37, %38, %39, %40, %41, %42, %43, %44, %45, %46, %47, "
    "%48, %49, %50, %51, %52, %53, %54, %55, %56, %57, %58, %59, %60, %61, %62, %63, "
    "%64, %65, %66, %67, %68, %69, %70, %71, %72, %73, %74, %75, %76, %77, %78, %79, "
    "%80, %81, %82, %83, %84, %85, %86, %87}, "
    "{%88, %89, %90, %91}, %92, p, 1, 1, 1;\n}\n"
    : "+f"(d[0]), "+f"(d[1]), "+f"(d[2]), "+f"(d[3]), "+f"(d[4]), "+f"(d[5]), "+f"(d[6]), "+f"(d[7]),
      "+f"(d[8]), "+f"(d[9]), "+f"(d[10]), "+f"(d[11]), "+f"(d[12]), "+f"(d[13]), "+f"(d[14]), "+f"(d[15]),
      "+f"(d[16]), "+f"(d[17]), "+f"(d[18]), "+f"(d[19]), "+f"(d[20]), "+f"(d[21]), "+f"(d[22]), "+f"(d[23]),
      "+f"(d[24]), "+f"(d[25]), "+f"(d[26]), "+f"(d[27]), "+f"(d[28]), "+f"(d[29]), "+f"(d[30]), "+f"(d[31]),
      "+f"(d[32]), "+f"(d[33]), "+f"(d[34]), "+f"(d[35]), "+f"(d[36]), "+f"(d[37]), "+f"(d[38]), "+f"(d[39]),
      "+f"(d[40]), "+f"(d[41]), "+f"(d[42]), "+f"(d[43]), "+f"(d[44]), "+f"(d[45]), "+f"(d[46]), "+f"(d[47]),
      "+f"(d[48]), "+f"(d[49]), "+f"(d[50]), "+f"(d[51]), "+f"(d[52]), "+f"(d[53]), "+f"(d[54]), "+f"(d[55]),
      "+f"(d[56]), "+f"(d[57]), "+f"(d[58]), "+f"(d[59]), "+f"(d[60]), "+f"(d[61]), "+f"(d[62]), "+f"(d[63]),
      "+f"(d[64]), "+f"(d[65]), "+f"(d[66]), "+f"(d[67]), "+f"(d[68]), "+f"(d[69]), "+f"(d[70]), "+f"(d[71]),
      "+f"(d[72]), "+f"(d[73]), "+f"(d[74]), "+f"(d[75]), "+f"(d[76]), "+f"(d[77]), "+f"(d[78]), "+f"(d[79]),
      "+f"(d[80]), "+f"(d[81]), "+f"(d[82]), "+f"(d[83]), "+f"(d[84]), "+f"(d[85]), "+f"(d[86]), "+f"(d[87])
    : "r"(a0), "r"(a1), "r"(a2), "r"(a3), "l"(descB), "r"(scaleD));
}

__device__ __forceinline__ void mma16816(float (&c)[4], uint32_t a0, uint32_t a1, uint32_t a2, uint32_t a3, uint32_t b0, uint32_t b1) {
  asm("mma.sync.aligned.m16n8k16.row.col.f32.bf16.bf16.f32 {%0,%1,%2,%3}, {%4,%5,%6,%7}, {%8,%9}, {%0,%1,%2,%3};"
      : "+f"(c[0]), "+f"(c[1]), "+f"(c[2]), "+f"(c[3])
      : "r"(a0), "r"(a1), "r"(a2), "r"(a3), "r"(b0), "r"(b1));
}
__device__ __forceinline__ void stmatrix_x4(uint32_t addr, uint32_t r0, uint32_t r1, uint32_t r2, uint32_t r3) {
  asm volatile("stmatrix.sync.aligned.m8n8.x4.shared.b16 [%0], {%1,%2,%3,%4};" ::"r"(addr), "r"(r0), "r"(r1), "r"(r2), "r"(r3) : "memory");
}
__device__ __forceinline__ void ldmatrix_x4_trans(uint32_t addr, uint32_t& r0, uint32_t& r1, uint32_t& r2, uint32_t& r3) {
  asm volatile("ldmatrix.sync.aligned.m8n8.x4.trans.shared.b16 {%0,%1,%2,%3}, [%4];"
               : "=r"(r0), "=r"(r1), "=r"(r2), "=r"(r3)
               : "r"(addr)
               : "memory");
}
__device__ __forceinline__ uint32_t pack_bf16(float lo, float hi) {
  uint32_t r;
  asm("cvt.rn.bf16x2.f32 %0, %1, %2;" : "=r"(r) : "f"(hi), "f"(lo));
  return r;
}
__device__ __forceinline__ float bf_lo(uint32_t v) { return __uint_as_float(v << 16); }
__device__ __forceinline__ float bf_hi(uint32_t v) { return __uint_as_float(v & 0xffff0000u); }
__device__ __forceinline__ float bf16r(float x) { return bf_lo(pack_bf16(x, 0.f)); }
__device__ __forceinline__ uint32_t hsub2_bf16(uint32_t a, uint32_t b) {
  uint32_t r;
  asm("sub.rn.bf16x2 %0, %1, %2;" : "=r"(r) : "r"(a), "r"(b));
  return r;
}
__device__ __forceinline__ uint32_t hadd2_bf16(uint32_t a, uint32_t b) {
  uint32_t r;
  asm("add.rn.bf16x2 %0, %1, %2;" : "=r"(r) : "r"(a), "r"(b));
  return r;
}
__device__ __forceinline__ uint32_t hmul2_bf16(uint32_t a, uint32_t b) {
  uint32_t r;
  asm("mul.rn.bf16x2 %0, %1, %2;" : "=r"(r) : "r"(a), "r"(b));
  return r;
}
__device__ __forceinline__ void ln_params(float mean, float var, uint32_t& m2, float& rinv) {
  m2 = pack_bf16(mean, mean);
  const float ve = bf16r(bf16r(var) + 1e-5f);
  rinv = 1.0f / bf16r(sqrtf(ve));
}
__device__ __forceinline__ float ex2_approx(float x) {
  float r;
  asm("ex2.approx.ftz.f32 %0, %1;" : "=f"(r) : "f"(x));
  return r;
}
__device__ __forceinline__ float rcp_approx(float x) {
  float r;
  asm("rcp.approx.ftz.f32 %0, %1;" : "=f"(r) : "f"(x));
  return r;
}
__device__ __forceinline__ uint32_t phi_pack(float a, float b) {
  const uint32_t t = pack_bf16(a, b);
  const uint32_t lin = hadd2_bf16(t, 0x3F803F80u);
  const uint32_t ex = pack_bf16(ex2_approx(bf_lo(t) * 1.4426950408889634f), ex2_approx(bf_hi(t) * 1.4426950408889634f));
  uint32_t mask;
  asm("set.gt.u32.bf16x2 %0, %1, %2;" : "=r"(mask) : "r"(t), "r"(0u));
  const uint32_t p = (lin & mask) | (ex & ~mask);
  return pack_bf16(bf_lo(p) + 1e-6f, bf_hi(p) + 1e-6f);
}
__device__ __forceinline__ uint4 ldg_nc(const uint4* p) {
  uint4 v;
  asm volatile("ld.global.nc.L1::no_allocate.v4.u32 {%0,%1,%2,%3}, [%4];" : "=r"(v.x), "=r"(v.y), "=r"(v.z), "=r"(v.w) : "l"(p));
  return v;
}
__device__ __forceinline__ float4 ldg_cg_f4(const float4* p) {
  float4 v;
  asm volatile("ld.global.cg.v4.f32 {%0,%1,%2,%3}, [%4];" : "=f"(v.x), "=f"(v.y), "=f"(v.z), "=f"(v.w) : "l"(p) : "memory");
  return v;
}
__device__ __forceinline__ uint4 ld_x(const uint4* p) {
  uint4 v;
  asm volatile("{\n.reg .b128 q;\nld.relaxed.gpu.global.b128 q, [%4];\nmov.b128 {%0,%1,%2,%3}, q;\n}\n"
               : "=r"(v.x), "=r"(v.y), "=r"(v.z), "=r"(v.w)
               : "l"(p)
               : "memory");
  return v;
}
__device__ __forceinline__ void st_x(uint4* p, uint32_t a, uint32_t b, uint32_t c, uint32_t d) {
  asm volatile("{\n.reg .b128 q;\nmov.b128 q, {%1,%2,%3,%4};\nst.relaxed.gpu.global.b128 [%0], q;\n}\n" ::"l"(p), "r"(a), "r"(b), "r"(c), "r"(d)
               : "memory");
}
__device__ __forceinline__ uint32_t ld_acquire(const uint32_t* p) {
  uint32_t v;
  asm volatile("ld.acquire.gpu.global.u32 %0, [%1];" : "=r"(v) : "l"(p) : "memory");
  return v;
}
__device__ __forceinline__ void red_add_v4(float4* p, float a, float b, float c, float d) {
  asm volatile("red.relaxed.gpu.global.add.v4.f32 [%0], {%1,%2,%3,%4};" ::"l"(p), "f"(a), "f"(b), "f"(c), "f"(d) : "memory");
}
__device__ __forceinline__ void named_bar(int id) { asm volatile("bar.sync %0, 128;" ::"r"(id) : "memory"); }
__device__ __forceinline__ uint32_t w4(const uint4& v, int i) { return i == 0 ? v.x : i == 1 ? v.y : i == 2 ? v.z : v.w; }

template <int N>
__device__ __forceinline__ void fetch(uint4* r, const uint4* p) {
#pragma unroll
  for (int i = 0; i < N; ++i) r[i] = ld_x(p + i * 32);
}
template <int N>
__device__ __forceinline__ bool any_poison(const uint4* r) {
  bool bad = false;
#pragma unroll
  for (int i = 0; i < N; ++i) bad |= (r[i].x == POISON);
  return __any_sync(0xffffffffu, bad);
}
template <int N>
__device__ __forceinline__ void ensure(uint4* r, const uint4* p) {
  if (__builtin_expect(any_poison<N>(r), 0)) {
#pragma unroll 1
    for (int it = 0; it < SPIN_LIMIT; ++it) {
      fetch<N>(r, p);
      if (!any_poison<N>(r)) break;
    }
  }
}

__device__ __forceinline__ void poll_sources(const uint4* base, int frags_per_src, int nsrc_mask, int lane) {
  const uint32_t* p = reinterpret_cast<const uint32_t*>(base + (((lane & nsrc_mask) + 1) * frags_per_src - 1) * 32 + 31);
  uint32_t v0, v1;
  asm volatile("ld.relaxed.gpu.global.u32 %0, [%1];" : "=r"(v0) : "l"(p) : "memory");
#pragma unroll 1
  for (int it = 0; it < SPIN_LIMIT; ++it) {
    asm volatile("ld.relaxed.gpu.global.u32 %0, [%1];" : "=r"(v1) : "l"(p) : "memory");
    if (!__any_sync(0xffffffffu, v0 == POISON)) break;
    asm volatile("ld.relaxed.gpu.global.u32 %0, [%1];" : "=r"(v0) : "l"(p) : "memory");
    if (!__any_sync(0xffffffffu, v1 == POISON)) break;
  }
}

struct Params {
  const __nv_bfloat16* x;
  const __nv_bfloat16* w_gate;
  const __nv_bfloat16* w_up;
  __nv_bfloat16* out;
};

__global__ void __launch_bounds__(384, 1)
fused_block_kernel(const __grid_constant__ CUtensorMap tm_qkv, const __grid_constant__ CUtensorMap tm_wo,
                   const __grid_constant__ CUtensorMap tm_down, const Params prm) {
  extern __shared__ __align__(1024) uint8_t smem[];
  const uint32_t sbase = smem_u32(smem);
  const int tid = threadIdx.x;
  const int warp = tid >> 5, lane = tid & 31;
  const int b = blockIdx.x;
  const int cm = b & 1, cp = b >> 1;
  const int tiA = 2 * (cp >> 3) + cm, tjA = cp & 7;
  const int rtB = 2 * (cp >> 2) + cm, jjB = cp & 3;
  const uint32_t bar_full = sbase + SM_BAR, bar_empty = sbase + SM_BAR + NSLOT * 8;
  const uint32_t bar_epoch = sbase + SM_EBAR;

  if (tid == 0) {
    for (int s = 0; s < NSLOT; ++s) {
      mbar_init(bar_full + s * 8, 1);
      mbar_init(bar_empty + s * 8, 4);
    }
    mbar_init(bar_epoch, 1);
    asm volatile("fence.mbarrier_init.release.cluster;" ::: "memory");
  }
  __syncthreads();
  asm volatile("barrier.cluster.arrive.relaxed.aligned;" ::: "memory");

  if (warp >= 8) {
    asm volatile("setmaxnreg.dec.sync.aligned.u32 40;");
    const int pw = warp - 8;
    auto issue = [&](int q) {
      const int slot = q % NSLOT;
      const uint32_t fb = bar_full + slot * 8, dst = sbase + slot * TILE_BYTES;
      if (q >= Q_VIRT && q < Q_GU) {
        mbar_arrive(fb);
        mbar_arrive_cluster(bar_empty + slot * 8, cm, 4);
        return;
      }
      mbar_expect_tx(fb, TILE_BYTES);
      if ((q & 1) != cm) return;
      if (q < Q_Q) {
        tma_5d_mc(dst, &tm_qkv, fb, DM * (1 + (q & 1)) + 64 * tjA, 2 * (q >> 1));
      } else if (q < Q_WO) {
        tma_5d_mc(dst, &tm_qkv, fb, 64 * tjA, 2 * (q - Q_Q));
      } else if (q < Q_VIRT) {
        const int r = (q - Q_WO) >> 1;
        tma_2d_mc(dst, &tm_wo, fb, 128 * jjB + 64 * (q & 1), 64 * ((r >> 1) + 4 * (r & 1)));
      } else if (q < Q_DN) {
        bulk_g2s_mc(dst, g_wgu + (size_t)(tjA * 48 + (q - Q_GU)) * 512, TILE_BYTES, fb);
      } else {
        tma_2d_mc(dst, &tm_down, fb, 128 * jjB + 64 * (q & 1), 64 * ((q - Q_DN) >> 1));
      }
    };
    if (pw == 0 && lane == 0) {
      uint32_t e;
      asm volatile("ld.relaxed.gpu.global.u32 %0, [%1];" : "=r"(e) : "l"(&g_epoch) : "memory");
      *reinterpret_cast<volatile uint32_t*>(smem + SM_MISC) = e;
      mbar_arrive(bar_epoch);
    }
    asm volatile("barrier.cluster.wait.aligned;" ::: "memory");
    if (lane == 0) {
#pragma unroll 1
      for (int q = pw; q < NSLOT; q += 4) issue(q);
    }
    __syncwarp();
    {
      const int rj = b & 7, rkt = (b >> 3) & 7, rm = b >> 6;
      const __nv_bfloat16* src = (rm ? prm.w_up : prm.w_gate) + (size_t)(64 * rkt) * FF + 176 * rj;
      uint4* dst = g_wgu + (size_t)((rj * 8 + rkt) * 6 + rm * 3) * 512;
      const int pt = tid - 256;
#pragma unroll 1
      for (int it = 0; it < 11; ++it) {
        const int idx = it * 128 + pt;
        const int r = idx / 22, cc = idx - r * 22;
        if (176 * rj + cc * 8 < FF) {
          const uint4 v = ldg_nc(reinterpret_cast<const uint4*>(src + (size_t)r * FF + cc * 8));
          dst[(cc >> 3) * 512 + r * 8 + ((cc & 7) ^ (r & 7))] = v;
        }
      }
      asm volatile("fence.proxy.async.global;" ::: "memory");
      asm volatile("bar.sync 3, 128;" ::: "memory");
      if (pt == 0) asm volatile("red.release.gpu.global.add.u32 [%0], 1;" ::"l"(&g_repack_cnt) : "memory");
    }
    if (lane == 0) {
      bool gu_ready = false;
#pragma unroll 1
      for (int q = NSLOT + pw; q < NTILES; q += 4) {
        mbar_wait(bar_empty + (q % NSLOT) * 8, ((q / NSLOT) - 1) & 1);
        if (q >= Q_GU && !gu_ready) {
          mbar_wait(bar_epoch, 0);
          const uint32_t target = 128u * (*reinterpret_cast<volatile uint32_t*>(smem + SM_MISC) + 1);
#pragma unroll 1
          for (int it = 0; it < SPIN_LIMIT; ++it)
            if ((int)(ld_acquire(&g_repack_cnt) - target) >= 0) break;
          asm volatile("fence.proxy.async.global;" ::: "memory");
          gu_ready = true;
        }
        issue(q);
      }
    }
    __syncwarp();
  } else {
    asm volatile("setmaxnreg.inc.sync.aligned.u32 232;");
    const int wg = warp >> 2, w = warp & 3;
    const int g = lane >> 2, t = lane & 3;
    const int tw = tid & 127;
    const uint32_t stage = sbase + SM_STAGE + wg * 16384;
    const uint32_t dlo = (sbase >> 4) | ((8192u >> 4) << 16);
    const int slabA = (2 * tiA + wg) * 4 + w, rowA = slabA * 16 + g;
    const int slabB = rtB * 4 + w, rowB = slabB * 16 + g, tjB = 2 * jjB + wg;
    auto wait_slot = [&](int slot, int parity) { mbar_wait(bar_full + slot * 8, parity); };
    auto rel_slots = [&](int slot, int n, int weight) {
      if (tw < 2 * n) mbar_arrive_cluster(bar_empty + (slot + (tw >> 1)) * 8, tw & 1, weight);
    };
    auto desc_at = [&](int slot, int ks) { return make_desc(dlo + slot * (TILE_BYTES >> 4) + ks * (2048 >> 4)); };

    uint32_t a[32][4];
    float r0, r1;
    {
      uint4 xa[16], xb[16];
      const uint4* px0 = reinterpret_cast<const uint4*>(prm.x + (size_t)rowA * DM) + t;
      const uint4* px1 = px0 + 8 * DM / 8;
#pragma unroll
      for (int kb = 0; kb < 16; ++kb) {
        xa[kb] = ldg_nc(px0 + kb * 4);
        xb[kb] = ldg_nc(px1 + kb * 4);
      }
#pragma unroll
      for (int q = 0; q < 4; ++q) {
        st_x(g_o + (slabA * 32 + 4 * tjA + q) * 32 + lane, POISON, POISON, POISON, POISON);
        st_x(g_h + (slabB * 32 + 4 * tjB + q) * 32 + lane, POISON, POISON, POISON, POISON);
      }
#pragma unroll
      for (int q = 0; q < 11; ++q) st_x(g_hh + (slabA * 88 + 11 * tjA + q) * 32 + lane, POISON, POISON, POISON, POISON);
      if (t < 2) reinterpret_cast<uint2*>(g_hstat)[(rowB + 8 * t) * 8 + tjB] = make_uint2(POISON, POISON);
      asm volatile("barrier.cluster.wait.aligned;" ::: "memory");
      TSTAMP(0);
      float s[2][4] = {}, q1[2][4] = {}, q2[2][4] = {};
      constexpr uint32_t ONES = 0x3F803F80u;
#pragma unroll
      for (int kb = 0; kb < 16; ++kb) {
#pragma unroll
        for (int sp = 0; sp < 2; ++sp) {
          const int k = 2 * kb + sp;
          a[k][0] = w4(xa[kb], 2 * sp);
          a[k][1] = w4(xb[kb], 2 * sp);
          a[k][2] = w4(xa[kb], 2 * sp + 1);
          a[k][3] = w4(xb[kb], 2 * sp + 1);
          mma16816(s[sp], a[k][0], a[k][1], a[k][2], a[k][3], ONES, ONES);
          mma16816(q1[sp], a[k][0], a[k][1], a[k][2], a[k][3], a[k][0], a[k][2]);
          mma16816(q2[sp], a[k][0], a[k][1], a[k][2], a[k][3], a[k][1], a[k][3]);
        }
      }
      const int srcl = g * 4 + (g >> 1);
      const float ssq0 = __shfl_sync(0xffffffffu, (g & 1) ? q1[0][1] + q1[1][1] : q1[0][0] + q1[1][0], srcl);
      const float ssq1 = __shfl_sync(0xffffffffu, (g & 1) ? q2[0][3] + q2[1][3] : q2[0][2] + q2[1][2], srcl);
      const float mean0 = (s[0][0] + s[1][0]) * (1.0f / DM), mean1 = (s[0][2] + s[1][2]) * (1.0f / DM);
      const float var0 = fmaxf(ssq0 * (1.0f / DM) - mean0 * mean0, 0.f);
      const float var1 = fmaxf(ssq1 * (1.0f / DM) - mean1 * mean1, 0.f);
      uint32_t m0, m1;
      ln_params(mean0, var0, m0, r0);
      ln_params(mean1, var1, m1, r1);
#pragma unroll
      for (int k = 0; k < 32; ++k) {
        a[k][0] = hsub2_bf16(a[k][0], m0);
        a[k][1] = hsub2_bf16(a[k][1], m1);
        a[k][2] = hsub2_bf16(a[k][2], m0);
        a[k][3] = hsub2_bf16(a[k][3], m1);
      }
      TSTAMP(1);
    }
    mbar_wait(bar_epoch, 0);
    const uint32_t epoch = *reinterpret_cast<volatile uint32_t*>(smem + SM_MISC);
    const uint32_t tag = epoch + 1;
    const int par = epoch & 1;
    {
      float acc[64];
#pragma unroll
      for (int kt = 0; kt < 8; ++kt) {
        wait_slot(Q_KV + 2 * kt, 0);
        wait_slot(Q_KV + 2 * kt + 1, 0);
        wgmma_fence();
#pragma unroll
        for (int ks = 0; ks < 4; ++ks) {
          const int k = 4 * kt + ks;
          wgmma_rs_n128(acc, a[k][0], a[k][1], a[k][2], a[k][3], desc_at(Q_KV + 2 * kt, ks), k > 0);
        }
        wgmma_commit();
        if (kt > 0) {
          wgmma_wait<1>();
          rel_slots(Q_KV + 2 * kt - 2, 2, 1);
        }
      }
      wgmma_wait<0>();
      rel_slots(Q_KV + 14, 2, 1);
      TSTAMP(2);

      {
        const int mrow = w * 16 + ((lane >> 3) & 1) * 8 + (lane & 7);
        const int mch = lane >> 4;
#pragma unroll
        for (int hh = 0; hh < 4; ++hh) {
          const uint32_t off = mrow * 128 + (((2 * hh + mch) ^ (mrow & 7)) << 4);
          stmatrix_x4(stage + off, phi_pack(acc[8 * hh + 0] * r0, acc[8 * hh + 1] * r0), phi_pack(acc[8 * hh + 2] * r1, acc[8 * hh + 3] * r1),
                      phi_pack(acc[8 * hh + 4] * r0, acc[8 * hh + 5] * r0), phi_pack(acc[8 * hh + 6] * r1, acc[8 * hh + 7] * r1));
          stmatrix_x4(stage + 8192 + off, pack_bf16(acc[32 + 8 * hh + 0] * r0, acc[32 + 8 * hh + 1] * r0),
                      pack_bf16(acc[32 + 8 * hh + 2] * r1, acc[32 + 8 * hh + 3] * r1),
                      pack_bf16(acc[32 + 8 * hh + 4] * r0, acc[32 + 8 * hh + 5] * r0),
                      pack_bf16(acc[32 + 8 * hh + 6] * r1, acc[32 + 8 * hh + 7] * r1));
        }
      }
      named_bar(1 + wg);
      {
        constexpr uint32_t ONES = 0x3F803F80u;
        float d0[4] = {}, d1[4] = {}, z0[4] = {}, z1[4] = {};
#pragma unroll
        for (int ks = 0; ks < 4; ++ks) {
          uint32_t va0, va1, va2, va3, pb0, pb1, pb2, pb3;
          {
            const int r = 16 * ks + (lane >> 4) * 8 + (lane & 7);
            const int ch = 2 * w + ((lane >> 3) & 1);
            ldmatrix_x4_trans(stage + 8192 + r * 128 + ((ch ^ (r & 7)) << 4), va0, va1, va2, va3);
          }
          {
            const int r = 16 * ks + ((lane >> 3) & 1) * 8 + (lane & 7);
            const int ch = 2 * w + (lane >> 4);
            ldmatrix_x4_trans(stage + r * 128 + ((ch ^ (r & 7)) << 4), pb0, pb1, pb2, pb3);
          }
          mma16816(d0, va0, va1, va2, va3, pb0, pb1);
          mma16816(d1, va0, va1, va2, va3, pb2, pb3);
          mma16816(z0, ONES, ONES, ONES, ONES, pb0, pb1);
          mma16816(z1, ONES, ONES, ONES, ONES, pb2, pb3);
        }
        const int head = 4 * tjA + w;
        float4* kvp = &g_kv[par][(head * 32 + lane) * 2];
        red_add_v4(kvp, d0[0], d0[1], d1[0], d1[1]);
        red_add_v4(kvp + 1, d0[2], d0[3], d1[2], d1[3]);
        if (g == 0) red_add_v4(&g_z[par][head * 4 + t], z0[0], z0[1], z1[0], z1[1]);
      }
      named_bar(1 + wg);
      if (tw == 0) asm volatile("red.release.gpu.global.add.u32 [%0], 1;" ::"l"(&g_kvcnt[tjA * 32]) : "memory");
      TSTAMP(3);
    }
    {
      uint32_t pq[4][4];
      {
        float accq[32];
#pragma unroll
        for (int kt = 0; kt < 8; ++kt) {
          wait_slot(Q_Q + kt, 0);
          wgmma_fence();
#pragma unroll
          for (int ks = 0; ks < 4; ++ks) {
            const int k = 4 * kt + ks;
            wgmma_rs_n64(accq, a[k][0], a[k][1], a[k][2], a[k][3], desc_at(Q_Q + kt, ks), k > 0);
          }
          wgmma_commit();
          if (kt > 0) {
            wgmma_wait<1>();
            rel_slots(Q_Q + kt - 1, 1, 1);
          }
        }
        wgmma_wait<0>();
        rel_slots(Q_Q + 7, 1, 1);
        TSTAMP(4);
#pragma unroll
        for (int hh = 0; hh < 4; ++hh) {
          pq[hh][0] = phi_pack(accq[8 * hh + 0] * r0, accq[8 * hh + 1] * r0);
          pq[hh][1] = phi_pack(accq[8 * hh + 2] * r1, accq[8 * hh + 3] * r1);
          pq[hh][2] = phi_pack(accq[8 * hh + 4] * r0, accq[8 * hh + 5] * r0);
          pq[hh][3] = phi_pack(accq[8 * hh + 6] * r1, accq[8 * hh + 7] * r1);
        }
      }
      if (b < 32) {
        g_kv[par ^ 1][b * 64 + (tid & 63)] = make_float4(0.f, 0.f, 0.f, 0.f);
        if (tid < 4) g_z[par ^ 1][b * 4 + tid] = make_float4(0.f, 0.f, 0.f, 0.f);
      }
      TSTAMP(5);
      {
        const uint32_t target = 32u * tag;
#pragma unroll 1
        for (int it = 0; it < SPIN_LIMIT; ++it) {
          uint32_t v = target;
          if (lane < 8) v = ld_acquire(&g_kvcnt[lane * 32]);
          if (__all_sync(0xffffffffu, (int)(v - target) >= 0)) break;
        }
        __syncwarp();
      }
      if (b == 0 && tid == 0) asm volatile("st.relaxed.gpu.global.u32 [%0], %1;" ::"l"(&g_epoch), "r"(tag) : "memory");
      TSTAMP(6);
#pragma unroll
      for (int hh = 0; hh < 4; ++hh) {
        const int head = 4 * tjA + hh;
        const float4 lo = ldg_cg_f4(&g_kv[par][(head * 32 + lane) * 2]), hi = ldg_cg_f4(&g_kv[par][(head * 32 + lane) * 2 + 1]);
        const float4 zz = ldg_cg_f4(&g_z[par][head * 4 + t]);
        float n0[4] = {}, n1[4] = {}, dn[4] = {};
        mma16816(dn, pq[hh][0], pq[hh][1], pq[hh][2], pq[hh][3], pack_bf16(zz.x, zz.y), pack_bf16(zz.z, zz.w));
        mma16816(n0, pq[hh][0], pq[hh][1], pq[hh][2], pq[hh][3], pack_bf16(lo.x, lo.y), pack_bf16(lo.z, lo.w));
        mma16816(n1, pq[hh][0], pq[hh][1], pq[hh][2], pq[hh][3], pack_bf16(hi.x, hi.y), pack_bf16(hi.z, hi.w));
        const float i0 = rcp_approx(dn[0] + 1e-6f), i1 = rcp_approx(dn[2] + 1e-6f);
        st_x(g_o + (slabA * 32 + head) * 32 + lane, pack_bf16(n0[0] * i0, n0[1] * i0), pack_bf16(n0[2] * i1, n0[3] * i1),
             pack_bf16(n1[0] * i0, n1[1] * i0), pack_bf16(n1[2] * i1, n1[3] * i1));
      }
      TSTAMP(7);
    }

    auto cross_reduce = [&](float (&acc)[64], float (&out)[32]) {
      float4* mine = reinterpret_cast<float4*>(smem + SM_STAGE + wg * 16384) + tw;
      const float4* theirs = reinterpret_cast<const float4*>(smem + SM_STAGE + (wg ^ 1) * 16384) + tw;
#pragma unroll
      for (int i = 0; i < 8; ++i) {
        const int o = wg ? 4 * i : 32 + 4 * i;
        mine[i * 128] = wg ? make_float4(acc[4 * i], acc[4 * i + 1], acc[4 * i + 2], acc[4 * i + 3])
                           : make_float4(acc[32 + 4 * i], acc[32 + 4 * i + 1], acc[32 + 4 * i + 2], acc[32 + 4 * i + 3]);
        (void)o;
      }
      asm volatile("bar.sync 4, 256;" ::: "memory");
#pragma unroll
      for (int i = 0; i < 8; ++i) {
        const float4 v = theirs[i * 128];
        out[4 * i + 0] = (wg ? acc[32 + 4 * i + 0] : acc[4 * i + 0]) + v.x;
        out[4 * i + 1] = (wg ? acc[32 + 4 * i + 1] : acc[4 * i + 1]) + v.y;
        out[4 * i + 2] = (wg ? acc[32 + 4 * i + 2] : acc[4 * i + 2]) + v.z;
        out[4 * i + 3] = (wg ? acc[32 + 4 * i + 3] : acc[4 * i + 3]) + v.w;
      }
    };

    {
      uint32_t xr[4][4];
#pragma unroll
      for (int q = 0; q < 4; ++q) {
        const uint32_t* p0 = reinterpret_cast<const uint32_t*>(prm.x + (size_t)rowB * DM + 64 * tjB + 16 * q + 2 * t);
        xr[q][0] = __ldg(p0);
        xr[q][1] = __ldg(p0 + 8 * DM / 2);
        xr[q][2] = __ldg(p0 + 4);
        xr[q][3] = __ldg(p0 + 8 * DM / 2 + 4);
      }
      const uint4* osrc = g_o + (slabB * 32 + 16 * wg) * 32;
      poll_sources(osrc, 4, 3, lane);
      uint4 of[16];
      fetch<16>(of, osrc + lane);
      float acc[64];
#pragma unroll
      for (int n = 0; n < 4; ++n) {
        const int slot = (Q_WO + 2 * (2 * n)) % NSLOT + 2 * wg;
        ensure<4>(&of[4 * n], osrc + lane + 4 * n * 32);
        wait_slot(slot, 1);
        wait_slot(slot + 1, 1);
        wgmma_fence();
#pragma unroll
        for (int ks = 0; ks < 4; ++ks)
          wgmma_rs_n128(acc, of[4 * n + ks].x, of[4 * n + ks].y, of[4 * n + ks].z, of[4 * n + ks].w, desc_at(slot, ks), (n | ks) > 0);
        wgmma_commit();
        if (n > 0) {
          wgmma_wait<1>();
          rel_slots(slot - 4, 2, 2);
        }
      }
      wgmma_wait<0>();
      rel_slots((Q_WO + 12) % NSLOT + 2 * wg, 2, 2);
      TSTAMP(8);
      float sum[32];
      cross_reduce(acc, sum);

      uint32_t hf[4][4];
      float s0 = 0.f, s1 = 0.f;
#pragma unroll
      for (int q = 0; q < 4; ++q) {
#pragma unroll
        for (int r = 0; r < 4; ++r) {
          hf[q][r] = hadd2_bf16(xr[q][r], pack_bf16(sum[8 * q + 2 * r], sum[8 * q + 2 * r + 1]));
          const float sv = bf_lo(hf[q][r]) + bf_hi(hf[q][r]);
          if (r & 1) s1 += sv; else s0 += sv;
        }
        st_x(g_h + (slabB * 32 + 4 * tjB + q) * 32 + lane, hf[q][0], hf[q][1], hf[q][2], hf[q][3]);
      }
      s0 += __shfl_xor_sync(0xffffffffu, s0, 1); s1 += __shfl_xor_sync(0xffffffffu, s1, 1);
      s0 += __shfl_xor_sync(0xffffffffu, s0, 2); s1 += __shfl_xor_sync(0xffffffffu, s1, 2);
      const float mu0 = s0 * (1.0f / 64), mu1 = s1 * (1.0f / 64);
      float e0 = 0.f, e1 = 0.f;
#pragma unroll
      for (int q = 0; q < 4; ++q) {
#pragma unroll
        for (int r = 0; r < 4; ++r) {
          const float mu = (r & 1) ? mu1 : mu0;
          const float dl = bf_lo(hf[q][r]) - mu, dh = bf_hi(hf[q][r]) - mu;
          const float sv = dl * dl + dh * dh;
          if (r & 1) e1 += sv; else e0 += sv;
        }
      }
      e0 += __shfl_xor_sync(0xffffffffu, e0, 1); e1 += __shfl_xor_sync(0xffffffffu, e1, 1);
      e0 += __shfl_xor_sync(0xffffffffu, e0, 2); e1 += __shfl_xor_sync(0xffffffffu, e1, 2);
      if (t < 2) {
        const uint64_t pk = t == 0 ? ((uint64_t)__float_as_uint(e0) << 32 | __float_as_uint(mu0)) : ((uint64_t)__float_as_uint(e1) << 32 | __float_as_uint(mu1));
        const uint64_t* dst = reinterpret_cast<const uint64_t*>(g_hstat) + (rowB + 8 * t) * 8 + tjB;
        asm volatile("st.relaxed.gpu.global.u64 [%0], %1;" ::"l"(dst), "l"(pk) : "memory");
      }
      TSTAMP(9);
    }

    {
      const uint4* hsrc = g_h + slabA * 32 * 32;
      uint4 hb[8];
      poll_sources(hsrc, 4, 7, lane);
      fetch<8>(hb, hsrc + lane);
      uint32_t m0, m1;
      {
        uint4 p0, p1;
#pragma unroll 1
        for (int it = 0; it < SPIN_LIMIT; ++it) {
          p0 = ld_x(&g_hstat[rowA * 4 + t]);
          p1 = ld_x(&g_hstat[(rowA + 8) * 4 + t]);
          const bool bad = p0.x == POISON || p0.z == POISON || p1.x == POISON || p1.z == POISON;
          if (!__any_sync(0xffffffffu, bad)) break;
        }
        TSTAMP(10);
        const float a0x = __uint_as_float(p0.x), a0y = __uint_as_float(p0.y), a0z = __uint_as_float(p0.z), a0w = __uint_as_float(p0.w);
        const float a1x = __uint_as_float(p1.x), a1y = __uint_as_float(p1.y), a1z = __uint_as_float(p1.z), a1w = __uint_as_float(p1.w);
        float a0 = a0x + a0z, a1 = a1x + a1z;
        a0 += __shfl_xor_sync(0xffffffffu, a0, 1); a1 += __shfl_xor_sync(0xffffffffu, a1, 1);
        a0 += __shfl_xor_sync(0xffffffffu, a0, 2); a1 += __shfl_xor_sync(0xffffffffu, a1, 2);
        const float mean0 = a0 * 0.125f, mean1 = a1 * 0.125f;
        float v0 = a0y + a0w + 64.f * ((a0x - mean0) * (a0x - mean0) + (a0z - mean0) * (a0z - mean0));
        float v1 = a1y + a1w + 64.f * ((a1x - mean1) * (a1x - mean1) + (a1z - mean1) * (a1z - mean1));
        v0 += __shfl_xor_sync(0xffffffffu, v0, 1); v1 += __shfl_xor_sync(0xffffffffu, v1, 1);
        v0 += __shfl_xor_sync(0xffffffffu, v0, 2); v1 += __shfl_xor_sync(0xffffffffu, v1, 2);
        ln_params(mean0, v0 * (1.0f / DM), m0, r0);
        ln_params(mean1, v1 * (1.0f / DM), m1, r1);
      }
      float accg[88], accu[88];
      uint32_t an[2][4];
      int sg = Q_GU % NSLOT;
      int q = Q_GU;
#pragma unroll 1
      for (int it = 0; it < 4; ++it) {
#pragma unroll
        for (int k8 = 0; k8 < 8; ++k8) {
          const int k = it * 8 + k8, ks = k8 & 3;
          const int su = sg + 3 >= NSLOT ? sg + 3 - NSLOT : sg + 3;
          if (ks == 0) {
            const int pg = (q / NSLOT) & 1, pu = ((q + 3) / NSLOT) & 1;
#pragma unroll
            for (int u = 0; u < 3; ++u) wait_slot(sg + u, pg);
#pragma unroll
            for (int u = 0; u < 3; ++u) wait_slot(su + u, pu);
          }
          ensure<1>(&hb[k8], hsrc + lane + k * 32);
          an[k8 & 1][0] = hsub2_bf16(hb[k8].x, m0);
          an[k8 & 1][1] = hsub2_bf16(hb[k8].y, m1);
          an[k8 & 1][2] = hsub2_bf16(hb[k8].z, m0);
          an[k8 & 1][3] = hsub2_bf16(hb[k8].w, m1);
          if (it < 3) hb[k8] = ld_x(hsrc + lane + (k + 8) * 32);
          wgmma_fence();
          wgmma_rs_n176(accg, an[k8 & 1][0], an[k8 & 1][1], an[k8 & 1][2], an[k8 & 1][3], desc_at(sg, ks), k > 0);
          wgmma_rs_n176(accu, an[k8 & 1][0], an[k8 & 1][1], an[k8 & 1][2], an[k8 & 1][3], desc_at(su, ks), k > 0);
          wgmma_commit();
          wgmma_wait<1>();
          if (ks == 0 && k > 0) {
            const int pgs = sg >= 6 ? sg - 6 : sg + NSLOT - 6;
            const int pus = pgs + 3 >= NSLOT ? pgs + 3 - NSLOT : pgs + 3;
            rel_slots(pgs, 3, 1);
            rel_slots(pus, 3, 1);
          }
          if (ks == 3) {
            sg = sg + 6 >= NSLOT ? sg + 6 - NSLOT : sg + 6;
            q += 6;
          }
        }
      }
      wgmma_wait<0>();
      {
        const int pgs = sg >= 6 ? sg - 6 : sg + NSLOT - 6;
        const int pus = pgs + 3 >= NSLOT ? pgs + 3 - NSLOT : pgs + 3;
        rel_slots(pgs, 3, 1);
        rel_slots(pus, 3, 1);
      }
      TSTAMP(11);
#pragma unroll
      for (int qq = 0; qq < 11; ++qq) {
        uint32_t v[4];
#pragma unroll
        for (int r = 0; r < 4; ++r) {
          const float sc = (r & 1) ? r1 : r0;
          v[r] = hmul2_bf16(pack_bf16(accg[8 * qq + 2 * r] * sc, accg[8 * qq + 2 * r + 1] * sc),
                            pack_bf16(accu[8 * qq + 2 * r] * sc, accu[8 * qq + 2 * r + 1] * sc));
        }
        st_x(g_hh + (slabA * 88 + 11 * tjA + qq) * 32 + lane, v[0], v[1], v[2], v[3]);
      }
      TSTAMP(12);
    }

    {
      const uint4* hsrc = g_hh + slabB * 88 * 32;
      constexpr int WIN = 6;
      uint4 hb[WIN][4];
      poll_sources(hsrc, 11, 7, lane);
      TSTAMP(13);
      hsrc += lane + 4 * wg * 32;
#pragma unroll
      for (int n = 0; n < WIN; ++n) fetch<4>(hb[n], hsrc + n * 8 * 32);
      float acc[64];
#pragma unroll
      for (int n = 0; n < 11; ++n) {
        const int q0 = Q_DN + 4 * n;
        const int slot = wg ? (q0 + 2) % NSLOT : q0 % NSLOT;
        const int parity = wg ? ((q0 + 2) / NSLOT) & 1 : (q0 / NSLOT) & 1;
        ensure<4>(hb[n % WIN], hsrc + n * 8 * 32);
        wait_slot(slot, parity);
        wait_slot(slot + 1, parity);
        wgmma_fence();
#pragma unroll
        for (int ks = 0; ks < 4; ++ks)
          wgmma_rs_n128(acc, hb[n % WIN][ks].x, hb[n % WIN][ks].y, hb[n % WIN][ks].z, hb[n % WIN][ks].w, desc_at(slot, ks), (n | ks) > 0);
        wgmma_commit();
        if (n > 0) {
          wgmma_wait<1>();
          rel_slots(wg ? (q0 - 2) % NSLOT : (q0 - 4) % NSLOT, 2, 2);
          if (n - 1 + WIN < 11) fetch<4>(hb[(n - 1) % WIN], hsrc + (n - 1 + WIN) * 8 * 32);
        }
      }
      uint4 hf[4];
#pragma unroll
      for (int q = 0; q < 4; ++q) hf[q] = g_h[(slabB * 32 + 4 * tjB + q) * 32 + lane];
      wgmma_wait<0>();
      TSTAMP(14);
      float sum[32];
      cross_reduce(acc, sum);
      asm volatile("bar.sync 4, 256;" ::: "memory");
      const uint32_t wst = stage + w * 2048;
      {
        const int mrow = ((lane >> 3) & 1) * 8 + (lane & 7);
        const int mch = lane >> 4;
#pragma unroll
        for (int q = 0; q < 4; ++q) {
          stmatrix_x4(wst + mrow * 128 + (((2 * q + mch) ^ (mrow & 7)) << 4),
                      hadd2_bf16(hf[q].x, pack_bf16(sum[8 * q + 0], sum[8 * q + 1])), hadd2_bf16(hf[q].y, pack_bf16(sum[8 * q + 2], sum[8 * q + 3])),
                      hadd2_bf16(hf[q].z, pack_bf16(sum[8 * q + 4], sum[8 * q + 5])), hadd2_bf16(hf[q].w, pack_bf16(sum[8 * q + 6], sum[8 * q + 7])));
        }
      }
      __syncwarp();
#pragma unroll
      for (int it = 0; it < 4; ++it) {
        const int r = it * 4 + (lane >> 3), ch = lane & 7;
        uint4 v;
        asm volatile("ld.shared.v4.u32 {%0,%1,%2,%3}, [%4];" : "=r"(v.x), "=r"(v.y), "=r"(v.z), "=r"(v.w) : "r"(wst + r * 128 + ((ch ^ (r & 7)) << 4)));
        *reinterpret_cast<uint4*>(prm.out + (size_t)(slabB * 16 + r) * DM + 64 * tjB + ch * 8) = v;
      }
      TSTAMP(15);
    }
  }
  asm volatile("barrier.cluster.arrive.relaxed.aligned;\nbarrier.cluster.wait.aligned;" ::: "memory");
}

typedef CUresult (*EncodeTiledFn)(CUtensorMap*, CUtensorMapDataType, cuuint32_t, void*, const cuuint64_t*, const cuuint64_t*,
                                  const cuuint32_t*, const cuuint32_t*, CUtensorMapInterleave, CUtensorMapSwizzle,
                                  CUtensorMapL2promotion, CUtensorMapFloatOOBfill);

void encode_2d(EncodeTiledFn enc, CUtensorMap* tm, const void* p, int rows, int cols) {
  cuuint64_t gd[2] = {(cuuint64_t)cols, (cuuint64_t)rows};
  cuuint64_t gs[1] = {(cuuint64_t)cols * 2};
  cuuint32_t bx[2] = {64, 64};
  cuuint32_t es[2] = {1, 1};
  enc(tm, CU_TENSOR_MAP_DATA_TYPE_BFLOAT16, 2, const_cast<void*>(p), gd, gs, bx, es, CU_TENSOR_MAP_INTERLEAVE_NONE,
      CU_TENSOR_MAP_SWIZZLE_128B, CU_TENSOR_MAP_L2_PROMOTION_L2_128B, CU_TENSOR_MAP_FLOAT_OOB_FILL_NONE);
}

}

extern "C" void kernel_launch(void* const* d_in, const int* in_sizes, int n_in, void* d_out, int out_size) {
  (void)in_sizes; (void)n_in; (void)out_size;
  static CUtensorMap tm_qkv, tm_wo, tm_down;
  static const void* cached[3] = {nullptr, nullptr, nullptr};
  static bool attr_done = false;
  const void* ptrs[3] = {d_in[1], d_in[2], d_in[6]};
  bool same = true;
  for (int i = 0; i < 3; ++i) same = same && (cached[i] == ptrs[i]);
  if (!same) {
    void* fn = nullptr;
    cudaDriverEntryPointQueryResult qr;
    cudaGetDriverEntryPoint("cuTensorMapEncodeTiled", &fn, cudaEnableDefault, &qr);
    EncodeTiledFn enc = (EncodeTiledFn)fn;
    {
      const cuuint64_t pitch = 3 * DM * 2;
      cuuint64_t gd[5] = {(cuuint64_t)3 * DM, 2, 4, 4, 16};
      cuuint64_t gs[4] = {pitch, 8 * pitch, 2 * pitch, 32 * pitch};
      cuuint32_t bx[5] = {64, 2, 4, 4, 2};
      cuuint32_t es[5] = {1, 1, 1, 1, 1};
      enc(&tm_qkv, CU_TENSOR_MAP_DATA_TYPE_BFLOAT16, 5, const_cast<void*>(ptrs[0]), gd, gs, bx, es, CU_TENSOR_MAP_INTERLEAVE_NONE,
          CU_TENSOR_MAP_SWIZZLE_128B, CU_TENSOR_MAP_L2_PROMOTION_L2_128B, CU_TENSOR_MAP_FLOAT_OOB_FILL_NONE);
    }
    encode_2d(enc, &tm_wo, ptrs[1], DM, DM);
    encode_2d(enc, &tm_down, ptrs[2], FF, DM);
    for (int i = 0; i < 3; ++i) cached[i] = ptrs[i];
  }
  if (!attr_done) {
    cudaFuncSetAttribute(fused_block_kernel, cudaFuncAttributeMaxDynamicSharedMemorySize, SM_TOTAL);
    attr_done = true;
  }
  Params prm;
  prm.x = (const __nv_bfloat16*)d_in[0];
  prm.w_gate = (const __nv_bfloat16*)d_in[4];
  prm.w_up = (const __nv_bfloat16*)d_in[5];
  prm.out = (__nv_bfloat16*)d_out;
  cudaLaunchConfig_t cfg = {};
  cfg.gridDim = dim3(NCTA);
  cfg.blockDim = dim3(384);
  cfg.dynamicSmemBytes = SM_TOTAL;
  cfg.stream = cudaStreamPerThread;
  cudaLaunchAttribute at[1];
  at[0].id = cudaLaunchAttributeClusterDimension;
  at[0].val.clusterDim.x = 2;
  at[0].val.clusterDim.y = 1;
  at[0].val.clusterDim.z = 1;
  cfg.attrs = at;
  cfg.numAttrs = 1;
  cudaLaunchKernelEx(&cfg, fused_block_kernel, tm_qkv, tm_wo, tm_down, prm);
}
```

```cpp
#include <cuda_runtime.h>
#include <cuda_bf16.h>
#include <cuda.h>
#include <stdint.h>
#include <type_traits>

namespace {

constexpr int DM = 512;
constexpr int FF = 1376;
constexpr int NCTA = 128;
constexpr int NST = 12;
constexpr int STAGE_BYTES = 16384;
constexpr int N_X = 0, N_KV = 8, N_Q = 16, N_WO = 20, N_GU = 28, N_DN = 52, NSTAGES = 76;

constexpr int SM_STAGE = NST * STAGE_BYTES;
constexpr int SM_BAR = SM_STAGE + 32768;
constexpr int SM_EBAR = SM_BAR + 2 * NST * 8;
constexpr int SM_KBAR = SM_EBAR + 8;
constexpr int SM_PBAR = SM_KBAR + 8;
constexpr int SM_UBAR = SM_PBAR + 24;
constexpr int SM_MISC = SM_UBAR + 64;
constexpr int SM_KVF = SM_MISC + 8;
constexpr int SM_TOTAL = SM_KVF + 4 * 544;

constexpr int SPIN_LIMIT = 1 << 18;
constexpr uint32_t POISON = 0xFFFFFFFFu;

__device__ uint4 g_o[128 * 32 * 32];
__device__ uint4 g_h[128 * 32 * 32];
__device__ uint4 g_hh[128 * 88 * 32];
__device__ uint4 g_hstat[2048 * 4];
__device__ float4 g_kv[2][32 * 32 * 2];
__device__ float4 g_z[2][32 * 4];
__device__ uint4 g_wgu[8 * 3 * 8 * 2 * 512];
__device__ uint32_t g_hhflag[32 * 3 * 8];
__device__ uint32_t g_kvcnt[8 * 32];
__device__ uint32_t g_epoch;
#define ATTR_BEGIN() do {} while (0)
#define ATTR_END(slotid) do {} while (0)
#define ATTR_FLUSH(base) do {} while (0)
#define XSTAMP(k) do {} while (0)
#define TSTAMP(k) do {} while (0)

__device__ __forceinline__ uint32_t smem_u32(const void* p) { return (uint32_t)__cvta_generic_to_shared(p); }
__device__ __forceinline__ void mbar_init(uint32_t bar, uint32_t cnt) {
  asm volatile("mbarrier.init.shared::cta.b64 [%0], %1;" ::"r"(bar), "r"(cnt) : "memory");
}
__device__ __forceinline__ void mbar_expect_tx(uint32_t bar, uint32_t bytes) {
  asm volatile("mbarrier.arrive.expect_tx.shared::cta.b64 _, [%0], %1;" ::"r"(bar), "r"(bytes) : "memory");
}
__device__ __forceinline__ void mbar_arrive(uint32_t bar) {
  asm volatile("mbarrier.arrive.shared::cta.b64 _, [%0];" ::"r"(bar) : "memory");
}
__device__ __forceinline__ void mbar_wait(uint32_t bar, uint32_t parity) {
  asm volatile(
      "{\n.reg .pred p;\n.reg .u32 c;\nmov.u32 c, 0;\n"
      "W%=:\nmbarrier.try_wait.parity.shared::cta.b64 p, [%0], %1;\n@p bra D%=;\n"
      "add.u32 c, c, 1;\nsetp.lt.u32 p, c, %2;\n@p bra W%=;\nD%=:\n}\n" ::"r"(bar), "r"(parity), "n"(SPIN_LIMIT)
      : "memory");
}
__device__ __forceinline__ void tma_3d_mc(uint32_t dst, const CUtensorMap* tm, uint32_t bar, int c1, int c2) {
  asm volatile(
      "cp.async.bulk.tensor.3d.shared::cluster.global.mbarrier::complete_tx::bytes.multicast::cluster [%0], [%1, {%3, %4, %5}], [%2], %6;" ::"r"(dst),
      "l"((uint64_t)tm), "r"(bar), "r"(0), "r"(c1), "r"(c2), "h"((uint16_t)3)
      : "memory");
}
__device__ __forceinline__ void tma_3d(uint32_t dst, const CUtensorMap* tm, uint32_t bar, int c1, int c2) {
  asm volatile(
      "cp.async.bulk.tensor.3d.shared::cluster.global.mbarrier::complete_tx::bytes [%0], [%1, {%3, %4, %5}], [%2];" ::"r"(dst),
      "l"((uint64_t)tm), "r"(bar), "r"(0), "r"(c1), "r"(c2)
      : "memory");
}
__device__ __forceinline__ void bulk_g2s_mc(uint32_t dst, const void* src, uint32_t bytes, uint32_t bar) {
  asm volatile("cp.async.bulk.shared::cluster.global.mbarrier::complete_tx::bytes.multicast::cluster [%0], [%1], %2, [%3], %4;" ::"r"(dst),
               "l"(src), "r"(bytes), "r"(bar), "h"((uint16_t)3)
               : "memory");
}
__device__ __forceinline__ void mbar_arrive_cluster(uint32_t bar, uint32_t rank, uint32_t count) {
  asm volatile(
      "{\n.reg .b32 ra;\nmapa.shared::cluster.u32 ra, %0, %1;\nmbarrier.arrive.shared::cluster.b64 _, [ra], %2;\n}\n" ::"r"(bar), "r"(rank), "r"(count)
      : "memory");
}
__device__ __forceinline__ void wgmma_fence() { asm volatile("wgmma.fence.sync.aligned;" ::: "memory"); }
__device__ __forceinline__ void wgmma_commit() { asm volatile("wgmma.commit_group.sync.aligned;" ::: "memory"); }
template <int N>
__device__ __forceinline__ void wgmma_wait() { asm volatile("wgmma.wait_group.sync.aligned %0;" ::"n"(N) : "memory"); }

__device__ __forceinline__ uint64_t make_desc(uint32_t lo) {
  return (uint64_t)lo | ((uint64_t)((1024u >> 4) | (1u << 30)) << 32);
}

__device__ __forceinline__ void wgmma_rs_n64(float (&d)[32], uint32_t a0, uint32_t a1, uint32_t a2, uint32_t a3, uint64_t descB, int scaleD) {
  asm volatile(
    "{\n.reg .pred p;\nsetp.ne.b32 p, %37, 0;\n"
    "wgmma.mma_async.sync.aligned.m64n64k16.f32.bf16.bf16 "
    "{%0, %1, %2, %3, %4, %5, %6, %7, %8, %9, %10, %11, %12, %13, %14, %15, "
    "%16, %17, %18, %19, %20, %21, %22, %23, %24, %25, %26, %27, %28, %29, %30, %31}, "
    "{%32, %33, %34, %35}, %36, p, 1, 1, 1;\n}\n"
    : "+f"(d[0]), "+f"(d[1]), "+f"(d[2]), "+f"(d[3]), "+f"(d[4]), "+f"(d[5]), "+f"(d[6]), "+f"(d[7]),
      "+f"(d[8]), "+f"(d[9]), "+f"(d[10]), "+f"(d[11]), "+f"(d[12]), "+f"(d[13]), "+f"(d[14]), "+f"(d[15]),
      "+f"(d[16]), "+f"(d[17]), "+f"(d[18]), "+f"(d[19]), "+f"(d[20]), "+f"(d[21]), "+f"(d[22]), "+f"(d[23]),
      "+f"(d[24]), "+f"(d[25]), "+f"(d[26]), "+f"(d[27]), "+f"(d[28]), "+f"(d[29]), "+f"(d[30]), "+f"(d[31])
    : "r"(a0), "r"(a1), "r"(a2), "r"(a3), "l"(descB), "r"(scaleD));
}

__device__ __forceinline__ void wgmma_rs_n112(float (&d)[56], uint32_t a0, uint32_t a1, uint32_t a2, uint32_t a3, uint64_t descB, int scaleD) {
  asm volatile(
    "{\n.reg .pred p;\nsetp.ne.b32 p, %61, 0;\n"
    "wgmma.mma_async.sync.aligned.m64n112k16.f32.bf16.bf16 "
    "{%0, %1, %2, %3, %4, %5, %6, %7, %8, %9, %10, %11, %12, %13, %14, %15, "
    "%16, %17, %18, %19, %20, %21, %22, %23, %24, %25, %26, %27, %28, %29, %30, %31, "
    "%32, %33, %34, %35, %36, %37, %38, %39, %40, %41, %42, %43, %44, %45, %46, %47, "
    "%48, %49, %50, %51, %52, %53, %54, %55}, "
    "{%56, %57, %58, %59}, %60, p, 1, 1, 1;\n}\n"
    : "+f"(d[0]), "+f"(d[1]), "+f"(d[2]), "+f"(d[3]), "+f"(d[4]), "+f"(d[5]), "+f"(d[6]), "+f"(d[7]),
      "+f"(d[8]), "+f"(d[9]), "+f"(d[10]), "+f"(d[11]), "+f"(d[12]), "+f"(d[13]), "+f"(d[14]), "+f"(d[15]),
      "+f"(d[16]), "+f"(d[17]), "+f"(d[18]), "+f"(d[19]), "+f"(d[20]), "+f"(d[21]), "+f"(d[22]), "+f"(d[23]),
      "+f"(d[24]), "+f"(d[25]), "+f"(d[26]), "+f"(d[27]), "+f"(d[28]), "+f"(d[29]), "+f"(d[30]), "+f"(d[31]),
      "+f"(d[32]), "+f"(d[33]), "+f"(d[34]), "+f"(d[35]), "+f"(d[36]), "+f"(d[37]), "+f"(d[38]), "+f"(d[39]),
      "+f"(d[40]), "+f"(d[41]), "+f"(d[42]), "+f"(d[43]), "+f"(d[44]), "+f"(d[45]), "+f"(d[46]), "+f"(d[47]),
      "+f"(d[48]), "+f"(d[49]), "+f"(d[50]), "+f"(d[51]), "+f"(d[52]), "+f"(d[53]), "+f"(d[54]), "+f"(d[55])
    : "r"(a0), "r"(a1), "r"(a2), "r"(a3), "l"(descB), "r"(scaleD));
}

__device__ __forceinline__ void wgmma_rs_n128(float (&d)[64], uint32_t a0, uint32_t a1, uint32_t a2, uint32_t a3, uint64_t descB, int scaleD) {
  asm volatile(
    "{\n.reg .pred p;\nsetp.ne.b32 p, %69, 0;\n"
    "wgmma.mma_async.sync.aligned.m64n128k16.f32.bf16.bf16 "
    "{%0, %1, %2, %3, %4, %5, %6, %7, %8, %9, %10, %11, %12, %13, %14, %15, "
    "%16, %17, %18, %19, %20, %21, %22, %23, %24, %25, %26, %27, %28, %29, %30, %31, "
    "%32, %33, %34, %35, %36, %37, %38, %39, %40, %41, %42, %43, %44, %45, %46, %47, "
    "%48, %49, %50, %51, %52, %53, %54, %55, %56, %57, %58, %59, %60, %61, %62, %63}, "
    "{%64, %65, %66, %67}, %68, p, 1, 1, 1;\n}\n"
    : "+f"(d[0]), "+f"(d[1]), "+f"(d[2]), "+f"(d[3]), "+f"(d[4]), "+f"(d[5]), "+f"(d[6]), "+f"(d[7]),
      "+f"(d[8]), "+f"(d[9]), "+f"(d[10]), "+f"(d[11]), "+f"(d[12]), "+f"(d[13]), "+f"(d[14]), "+f"(d[15]),
      "+f"(d[16]), "+f"(d[17]), "+f"(d[18]), "+f"(d[19]), "+f"(d[20]), "+f"(d[21]), "+f"(d[22]), "+f"(d[23]),
      "+f"(d[24]), "+f"(d[25]), "+f"(d[26]), "+f"(d[27]), "+f"(d[28]), "+f"(d[29]), "+f"(d[30]), "+f"(d[31]),
      "+f"(d[32]), "+f"(d[33]), "+f"(d[34]), "+f"(d[35]), "+f"(d[36]), "+f"(d[37]), "+f"(d[38]), "+f"(d[39]),
      "+f"(d[40]), "+f"(d[41]), "+f"(d[42]), "+f"(d[43]), "+f"(d[44]), "+f"(d[45]), "+f"(d[46]), "+f"(d[47]),
      "+f"(d[48]), "+f"(d[49]), "+f"(d[50]), "+f"(d[51]), "+f"(d[52]), "+f"(d[53]), "+f"(d[54]), "+f"(d[55]),
      "+f"(d[56]), "+f"(d[57]), "+f"(d[58]), "+f"(d[59]), "+f"(d[60]), "+f"(d[61]), "+f"(d[62]), "+f"(d[63])
    : "r"(a0), "r"(a1), "r"(a2), "r"(a3), "l"(descB), "r"(scaleD));
}

__device__ __forceinline__ void mma16816(float (&c)[4], uint32_t a0, uint32_t a1, uint32_t a2, uint32_t a3, uint32_t b0, uint32_t b1) {
  asm("mma.sync.aligned.m16n8k16.row.col.f32.bf16.bf16.f32 {%0,%1,%2,%3}, {%4,%5,%6,%7}, {%8,%9}, {%0,%1,%2,%3};"
      : "+f"(c[0]), "+f"(c[1]), "+f"(c[2]), "+f"(c[3])
      : "r"(a0), "r"(a1), "r"(a2), "r"(a3), "r"(b0), "r"(b1));
}
__device__ __forceinline__ void stmatrix_x4(uint32_t addr, uint32_t r0, uint32_t r1, uint32_t r2, uint32_t r3) {
  asm volatile("stmatrix.sync.aligned.m8n8.x4.shared.b16 [%0], {%1,%2,%3,%4};" ::"r"(addr), "r"(r0), "r"(r1), "r"(r2), "r"(r3) : "memory");
}
__device__ __forceinline__ void ldmatrix_x4(uint32_t addr, uint32_t& r0, uint32_t& r1, uint32_t& r2, uint32_t& r3) {
  asm volatile("ldmatrix.sync.aligned.m8n8.x4.shared.b16 {%0,%1,%2,%3}, [%4];"
               : "=r"(r0), "=r"(r1), "=r"(r2), "=r"(r3)
               : "r"(addr)
               : "memory");
}
__device__ __forceinline__ void ldmatrix_x4_trans(uint32_t addr, uint32_t& r0, uint32_t& r1, uint32_t& r2, uint32_t& r3) {
  asm volatile("ldmatrix.sync.aligned.m8n8.x4.trans.shared.b16 {%0,%1,%2,%3}, [%4];"
               : "=r"(r0), "=r"(r1), "=r"(r2), "=r"(r3)
               : "r"(addr)
               : "memory");
}
__device__ __forceinline__ uint32_t pack_bf16(float lo, float hi) {
  uint32_t r;
  asm("cvt.rn.bf16x2.f32 %0, %1, %2;" : "=r"(r) : "f"(hi), "f"(lo));
  return r;
}
__device__ __forceinline__ float bf_lo(uint32_t v) { return __uint_as_float(v << 16); }
__device__ __forceinline__ float bf_hi(uint32_t v) { return __uint_as_float(v & 0xffff0000u); }
__device__ __forceinline__ float bf16r(float x) { return bf_lo(pack_bf16(x, 0.f)); }
__device__ __forceinline__ uint32_t hsub2_bf16(uint32_t a, uint32_t b) {
  uint32_t r;
  asm("sub.rn.bf16x2 %0, %1, %2;" : "=r"(r) : "r"(a), "r"(b));
  return r;
}
__device__ __forceinline__ uint32_t hadd2_bf16(uint32_t a, uint32_t b) {
  uint32_t r;
  asm("add.rn.bf16x2 %0, %1, %2;" : "=r"(r) : "r"(a), "r"(b));
  return r;
}
__device__ __forceinline__ uint32_t hmul2_bf16(uint32_t a, uint32_t b) {
  uint32_t r;
  asm("mul.rn.bf16x2 %0, %1, %2;" : "=r"(r) : "r"(a), "r"(b));
  return r;
}
__device__ __forceinline__ void ln_params(float mean, float var, uint32_t& m2, float& rinv) {
  m2 = pack_bf16(mean, mean);
  const float ve = bf16r(bf16r(var) + 1e-5f);
  rinv = 1.0f / bf16r(sqrtf(ve));
}
__device__ __forceinline__ float ex2_approx(float x) {
  float r;
  asm("ex2.approx.ftz.f32 %0, %1;" : "=f"(r) : "f"(x));
  return r;
}
__device__ __forceinline__ float rcp_approx(float x) {
  float r;
  asm("rcp.approx.ftz.f32 %0, %1;" : "=f"(r) : "f"(x));
  return r;
}
__device__ __forceinline__ uint32_t phi_pack(float a, float b) {
  const uint32_t t = pack_bf16(a, b);
  const uint32_t lin = hadd2_bf16(t, 0x3F803F80u);
  const uint32_t ex = pack_bf16(ex2_approx(bf_lo(t) * 1.4426950408889634f), ex2_approx(bf_hi(t) * 1.4426950408889634f));
  uint32_t mask;
  asm("set.gt.u32.bf16x2 %0, %1, %2;" : "=r"(mask) : "r"(t), "r"(0u));
  const uint32_t p = (lin & mask) | (ex & ~mask);
  return hadd2_bf16(p, 0x35863586u);
}
__device__ __forceinline__ uint4 ldg_nc(const uint4* p) {
  uint4 v;
  asm volatile("ld.global.nc.L1::no_allocate.v4.u32 {%0,%1,%2,%3}, [%4];" : "=r"(v.x), "=r"(v.y), "=r"(v.z), "=r"(v.w) : "l"(p));
  return v;
}
__device__ __forceinline__ uint4 ldg_cg(const uint4* p) {
  uint4 v;
  asm volatile("ld.global.cg.v4.u32 {%0,%1,%2,%3}, [%4];" : "=r"(v.x), "=r"(v.y), "=r"(v.z), "=r"(v.w) : "l"(p) : "memory");
  return v;
}
__device__ __forceinline__ float4 ldg_cg_f4(const float4* p) {
  float4 v;
  asm volatile("ld.global.cg.v4.f32 {%0,%1,%2,%3}, [%4];" : "=f"(v.x), "=f"(v.y), "=f"(v.z), "=f"(v.w) : "l"(p) : "memory");
  return v;
}
__device__ __forceinline__ uint4 ld_x(const uint4* p) {
  uint4 v;
  asm volatile("{\n.reg .b128 q;\nld.relaxed.gpu.global.b128 q, [%4];\nmov.b128 {%0,%1,%2,%3}, q;\n}\n"
               : "=r"(v.x), "=r"(v.y), "=r"(v.z), "=r"(v.w)
               : "l"(p)
               : "memory");
  return v;
}
__device__ __forceinline__ void st_x(uint4* p, uint32_t a, uint32_t b, uint32_t c, uint32_t d) {
  asm volatile("{\n.reg .b128 q;\nmov.b128 q, {%1,%2,%3,%4};\nst.relaxed.gpu.global.b128 [%0], q;\n}\n" ::"l"(p), "r"(a), "r"(b), "r"(c), "r"(d)
               : "memory");
}
__device__ __forceinline__ uint32_t ld_acquire(const uint32_t* p) {
  uint32_t v;
  asm volatile("ld.acquire.gpu.global.u32 %0, [%1];" : "=r"(v) : "l"(p) : "memory");
  return v;
}
__device__ __forceinline__ void red_add_v4(float4* p, float a, float b, float c, float d) {
  asm volatile("red.relaxed.gpu.global.add.v4.f32 [%0], {%1,%2,%3,%4};" ::"l"(p), "f"(a), "f"(b), "f"(c), "f"(d) : "memory");
}
__device__ __forceinline__ void named_bar(int id) { asm volatile("bar.sync %0, 128;" ::"r"(id) : "memory"); }

template <int N>
__device__ __forceinline__ void fetch(uint4* r, const uint4* p) {
#pragma unroll
  for (int i = 0; i < N; ++i) r[i] = ld_x(p + i * 32);
}
template <int N>
__device__ __forceinline__ bool any_poison(const uint4* r) {
  bool bad = false;
#pragma unroll
  for (int i = 0; i < N; ++i) bad |= (r[i].x == POISON);
  return __any_sync(0xffffffffu, bad);
}
template <int N>
__device__ __forceinline__ void ensure(uint4* r, const uint4* p) {
  if (__builtin_expect(any_poison<N>(r), 0)) {
#pragma unroll 1
    for (int it = 0; it < SPIN_LIMIT; ++it) {
      fetch<N>(r, p);
      if (!any_poison<N>(r)) break;
    }
  }
}

__device__ __forceinline__ void poll_sources(const uint4* base, int frags_per_src, int nsrc_mask, int lane) {
  const uint32_t* p = reinterpret_cast<const uint32_t*>(base + (((lane & nsrc_mask) + 1) * frags_per_src - 1) * 32 + 31);
  uint32_t v0, v1;
  asm volatile("ld.relaxed.gpu.global.u32 %0, [%1];" : "=r"(v0) : "l"(p) : "memory");
#pragma unroll 1
  for (int it = 0; it < SPIN_LIMIT; ++it) {
    asm volatile("ld.relaxed.gpu.global.u32 %0, [%1];" : "=r"(v1) : "l"(p) : "memory");
    if (!__any_sync(0xffffffffu, v0 == POISON)) break;
    asm volatile("ld.relaxed.gpu.global.u32 %0, [%1];" : "=r"(v0) : "l"(p) : "memory");
    if (!__any_sync(0xffffffffu, v1 == POISON)) break;
  }
}

struct Params {
  const __nv_bfloat16* x;
  const __nv_bfloat16* w_gate;
  const __nv_bfloat16* w_up;
  __nv_bfloat16* out;
};

__global__ void __launch_bounds__(384, 1)
fused_block_kernel(const __grid_constant__ CUtensorMap tm_x, const __grid_constant__ CUtensorMap tm_qkv, const __grid_constant__ CUtensorMap tm_wo,
                   const __grid_constant__ CUtensorMap tm_down64, const __grid_constant__ CUtensorMap tm_down48, const Params prm) {
  extern __shared__ __align__(1024) uint8_t smem[];
  const uint32_t sbase = smem_u32(smem);
  const int tid = threadIdx.x;
  const int warp = tid >> 5, lane = tid & 31;
  const int b = blockIdx.x;
  const int cm = b & 1, cp = b >> 1;
  const int ti1 = cp >> 2, tj1 = 2 * (cp & 3) + cm;
  const int tiA = 2 * (cp >> 3) + cm, tjA = cp & 7;
  const int rtB = 2 * (cp >> 2) + cm, jjB = cp & 3;
  const uint32_t bar_full = sbase + SM_BAR, bar_empty = sbase + SM_BAR + NST * 8;
  const uint32_t bar_epoch = sbase + SM_EBAR, bar_kv = sbase + SM_KBAR, bar_pass = sbase + SM_PBAR, bar_pub = sbase + SM_UBAR;

  if (tid == 256) {
    asm volatile("prefetch.tensormap [%0];" ::"l"((uint64_t)&tm_x) : "memory");
    asm volatile("prefetch.tensormap [%0];" ::"l"((uint64_t)&tm_qkv) : "memory");
    asm volatile("prefetch.tensormap [%0];" ::"l"((uint64_t)&tm_wo) : "memory");
    asm volatile("prefetch.tensormap [%0];" ::"l"((uint64_t)&tm_down64) : "memory");
    asm volatile("prefetch.tensormap [%0];" ::"l"((uint64_t)&tm_down48) : "memory");
  }
  if (tid == 0) {
    for (int s = 0; s < NST; ++s) {
      mbar_init(bar_full + s * 8, 1);
      mbar_init(bar_empty + s * 8, 4);
    }
    mbar_init(bar_epoch, 1);
    mbar_init(bar_kv, 1);
    for (int p = 0; p < 3; ++p) mbar_init(bar_pass + p * 8, 1);
    for (int p = 0; p < 8; ++p) mbar_init(bar_pub + p * 8, 4);
    asm volatile("fence.mbarrier_init.release.cluster;" ::: "memory");
  }
  __syncthreads();
  asm volatile("barrier.cluster.arrive.relaxed.aligned;" ::: "memory");

  if (warp >= 8) {
    asm volatile("setmaxnreg.dec.sync.aligned.u32 40;");
    const int pw = warp - 8;
    if (pw == 2 && lane == 0) {
      uint32_t e;
      asm volatile("ld.relaxed.gpu.global.u32 %0, [%1];" : "=r"(e) : "l"(&g_epoch) : "memory");
      *reinterpret_cast<volatile uint32_t*>(smem + SM_MISC) = e;
      mbar_arrive(bar_epoch);
    }
    asm volatile("barrier.cluster.wait.aligned;" ::: "memory");
    if (pw < 2) {
      if (lane == 0) {
        bool gu_ready = false;
#pragma unroll 1
        for (int n = pw; n < NSTAGES; n += 2) {
          const int st = n % NST;
          const uint32_t fb = bar_full + st * 8, dst = sbase + st * STAGE_BYTES;
          if (n >= NST) mbar_wait(bar_empty + st * 8, ((n / NST) - 1) & 1);
          if (n == N_KV + pw) mbar_wait(bar_full + (N_X + 4 + pw) * 8, 0);
          const bool short_tile = n >= N_DN + 16;
          mbar_expect_tx(fb, short_tile ? 12288 : STAGE_BYTES);
          if (n >= N_KV && n < N_WO) {
            if (n < N_Q) {
              tma_3d(dst, &tm_qkv, fb, 64 * (n - N_KV), 8 + tj1);
              tma_3d(dst + 8192, &tm_qkv, fb, 64 * (n - N_KV), 16 + tj1);
            } else {
              tma_3d(dst, &tm_qkv, fb, 128 * (n - N_Q), tj1);
              tma_3d(dst + 8192, &tm_qkv, fb, 128 * (n - N_Q) + 64, tj1);
            }
            continue;
          }
          if (pw != cm) continue;
          if (n < N_KV) {
            tma_3d_mc(dst, &tm_x, fb, (2 * ti1 + (n & 1)) * 64, 2 * (n >> 1));
          } else if (n < N_GU) {
            const int r = n - N_WO;
            tma_3d_mc(dst, &tm_wo, fb, 64 * ((r >> 1) + 4 * (r & 1)), 2 * jjB);
          } else if (n < N_DN) {
            if (!gu_ready) {
              mbar_wait(bar_kv, 0);
              asm volatile("fence.proxy.async.global;" ::: "memory");
              gu_ready = true;
            }
            bulk_g2s_mc(dst, g_wgu + (size_t)(tjA * 24 + (n - N_GU)) * 1024, STAGE_BYTES, fb);
          } else {
            const int u = n - N_DN;
            if (short_tile) {
              tma_3d_mc(dst, &tm_down48, fb, 176 * (u & 7) + 128, 2 * jjB);
              tma_3d_mc(dst + 8192, &tm_down48, fb, 176 * (u & 7) + 128, 2 * jjB + 1);
            } else {
              tma_3d_mc(dst, &tm_down64, fb, 176 * (u & 7) + 64 * (u >> 3), 2 * jjB);
            }
          }
        }
      }
      __syncwarp();
    } else {
      const int wg = pw - 2;
      {
        const int tjB = 2 * jjB + wg;
#pragma unroll 1
        for (int w = 0; w < 4; ++w) {
          const int slab1 = (2 * ti1 + wg) * 4 + w, slabB = rtB * 4 + w;
#pragma unroll
          for (int q = 0; q < 4; ++q) {
            g_o[(slab1 * 32 + 4 * tj1 + q) * 32 + lane] = make_uint4(POISON, POISON, POISON, POISON);
            g_h[(slabB * 32 + 4 * tjB + q) * 32 + lane] = make_uint4(POISON, POISON, POISON, POISON);
          }
          if (lane < 16) reinterpret_cast<uint2*>(g_hstat)[(slabB * 16 + lane) * 8 + tjB] = make_uint2(POISON, POISON);
        }
      }
      asm volatile("bar.sync 9, 64;" ::: "memory");
      mbar_wait(bar_epoch, 0);
      const uint32_t tag = *reinterpret_cast<volatile uint32_t*>(smem + SM_MISC) + 1;
      if (wg == 0) {
#pragma unroll 1
        for (int v = 0; v < 2; ++v) {
          mbar_wait(bar_pub + v * 8, 0);
          if (lane == 0) asm volatile("red.release.gpu.global.add.u32 [%0], 1;" ::"l"(&g_kvcnt[tj1 * 32]) : "memory");
        }
        const uint32_t target = 32u * tag;
#pragma unroll 1
        for (int it = 0; it < SPIN_LIMIT; ++it) {
          uint32_t v = target;
          if (lane < 8) v = ld_acquire(&g_kvcnt[lane * 32]);
          if (__all_sync(0xffffffffu, (int)(v - target) >= 0)) break;
        }
        __syncwarp();
        const int par = (tag - 1) & 1;
#pragma unroll
        for (int hh = 0; hh < 4; ++hh) {
          const int head = 4 * tj1 + hh;
          const float4 lo = ldg_cg_f4(&g_kv[par][(head * 32 + lane) * 2]), hi = ldg_cg_f4(&g_kv[par][(head * 32 + lane) * 2 + 1]);
          const float4 zz = ldg_cg_f4(&g_z[par][head * 4 + (lane & 3)]);
          *reinterpret_cast<uint4*>(smem + SM_KVF + hh * 544 + lane * 16) =
              make_uint4(pack_bf16(lo.x, lo.y), pack_bf16(lo.z, lo.w), pack_bf16(hi.x, hi.y), pack_bf16(hi.z, hi.w));
          if (lane < 4) *reinterpret_cast<uint2*>(smem + SM_KVF + hh * 544 + 512 + lane * 8) = make_uint2(pack_bf16(zz.x, zz.y), pack_bf16(zz.z, zz.w));
        }
        __syncwarp();
        if (lane == 0) mbar_arrive(bar_kv);
#pragma unroll 1
        for (int pv = 0; pv < 6; ++pv) {
          const int p = pv >> 1, v = pv & 1;
          mbar_wait(bar_pub + (2 + pv) * 8, 0);
          if (lane == 0) asm volatile("st.release.gpu.global.u32 [%0], %1;" ::"l"(&g_hhflag[((2 * tiA + v) * 3 + p) * 8 + tjA]), "r"(tag) : "memory");
        }
      } else {
        mbar_wait(bar_kv, 0);
#pragma unroll 1
        for (int p = 0; p < 3; ++p) {
          const uint32_t* f = &g_hhflag[(rtB * 3 + p) * 8 + (lane & 7)];
#pragma unroll 1
          for (int it = 0; it < SPIN_LIMIT; ++it) {
            if (__all_sync(0xffffffffu, ld_acquire(f) == tag)) break;
            __nanosleep(100);
          }
          __syncwarp();
          if (lane == 0) mbar_arrive(bar_pass + p * 8);
        }
      }
    }
  } else {
    asm volatile("setmaxnreg.inc.sync.aligned.u32 232;");
    const int wg = warp >> 2, w = warp & 3;
    const int g = lane >> 2, t = lane & 3;
    const int tw = tid & 127;
    const uint32_t stage = sbase + SM_STAGE + wg * 16384;
    const uint32_t dlo = ((sbase & 0x3FFFFu) >> 4) | ((8192u >> 4) << 16);
    const int slab1 = (2 * ti1 + wg) * 4 + w;
    const int slabA = (2 * tiA + wg) * 4 + w, rowA = slabA * 16 + g;
    const int slabB = rtB * 4 + w, rowB = slabB * 16 + g, tjB = 2 * jjB + wg;
    auto wait_stage = [&](int n) { ATTR_BEGIN(); mbar_wait(bar_full + (n % NST) * 8, (n / NST) & 1); ATTR_END(0); };
    auto wg_wait1 = [&]() { ATTR_BEGIN(); wgmma_wait<1>(); ATTR_END(2); };
    auto rel_stage = [&](int n, int weight) {
      if (tw < 2) mbar_arrive_cluster(bar_empty + (n % NST) * 8, tw, weight);
    };
    auto desc_at = [&](int n, int off) { return make_desc(dlo + (n % NST) * (STAGE_BYTES >> 4) + (off >> 4)); };
    auto order_wait = [&]() { asm volatile("bar.sync %0, 256;" ::"r"(7 + wg) : "memory"); };
    auto order_arrive = [&]() { asm volatile("bar.arrive %0, 256;" ::"r"(8 - wg) : "memory"); };
    if (wg == 1) order_arrive();
    auto publish = [&](int ev) { __syncwarp(); if (lane == 0) mbar_arrive(bar_pub + (2 * ev + wg) * 8); };

    uint32_t a[32][4];
    float r0, r1;
    {
      uint4 rp[6];
      {
        const __nv_bfloat16* src = ((b >> 6) ? prm.w_up : prm.w_gate) + (size_t)(64 * ((b >> 3) & 7)) * FF + 176 * (b & 7);
        const int nch = ((b & 7) == 7) ? 18 : 22;
#pragma unroll
        for (int u = 0; u < 6; ++u) {
          const int idx = u * 256 + tid;
          const int r = idx / 22, cc = idx - r * 22;
          rp[u] = make_uint4(0, 0, 0, 0);
          if (idx < 1408 && cc < nch) rp[u] = ldg_nc(reinterpret_cast<const uint4*>(src + (size_t)r * FF + cc * 8));
        }
      }
      asm volatile("barrier.cluster.wait.aligned;" ::: "memory");
      TSTAMP(0);
      float s[2][4] = {}, q1[2][4] = {}, q2[2][4] = {};
      float f0 = 0.f, f1 = 0.f, f2 = 0.f, f3 = 0.f;
      constexpr uint32_t ONES = 0x3F803F80u;
#pragma unroll
      for (int c = 0; c < 4; ++c) {
        const int n = N_X + 2 * c + wg;
        wait_stage(n);
        XSTAMP(c);
        const int xrow = w * 16 + ((lane >> 3) & 1) * 8 + (lane & 7);
        const uint32_t xs = sbase + (n % NST) * STAGE_BYTES + xrow * 128;
#pragma unroll
        for (int kk = 0; kk < 8; ++kk) {
          const int k = 8 * c + kk;
          ldmatrix_x4(xs + (kk >> 2) * 8192 + (((2 * (kk & 3) + (lane >> 4)) ^ (xrow & 7)) << 4), a[k][0], a[k][1], a[k][2], a[k][3]);
          mma16816(s[kk & 1], a[k][0], a[k][1], a[k][2], a[k][3], ONES, ONES);
          if (kk & 1) {
            f0 = fmaf(bf_lo(a[k][0]), bf_lo(a[k][0]), f0); f0 = fmaf(bf_hi(a[k][0]), bf_hi(a[k][0]), f0);
            f1 = fmaf(bf_lo(a[k][1]), bf_lo(a[k][1]), f1); f1 = fmaf(bf_hi(a[k][1]), bf_hi(a[k][1]), f1);
            f2 = fmaf(bf_lo(a[k][2]), bf_lo(a[k][2]), f2); f2 = fmaf(bf_hi(a[k][2]), bf_hi(a[k][2]), f2);
            f3 = fmaf(bf_lo(a[k][3]), bf_lo(a[k][3]), f3); f3 = fmaf(bf_hi(a[k][3]), bf_hi(a[k][3]), f3);
          } else {
            mma16816(q1[(kk >> 1) & 1], a[k][0], a[k][1], a[k][2], a[k][3], a[k][0], a[k][2]);
            mma16816(q2[(kk >> 1) & 1], a[k][0], a[k][1], a[k][2], a[k][3], a[k][1], a[k][3]);
          }
        }
        named_bar(1 + wg);
        rel_stage(n, 2);
      }
      XSTAMP(4);
      const int srcl = g * 4 + (g >> 1);
      f0 += f2; f1 += f3;
      f0 += __shfl_xor_sync(0xffffffffu, f0, 1); f1 += __shfl_xor_sync(0xffffffffu, f1, 1);
      f0 += __shfl_xor_sync(0xffffffffu, f0, 2); f1 += __shfl_xor_sync(0xffffffffu, f1, 2);
      const float ssq0 = f0 + __shfl_sync(0xffffffffu, (g & 1) ? q1[0][1] + q1[1][1] : q1[0][0] + q1[1][0], srcl);
      const float ssq1 = f1 + __shfl_sync(0xffffffffu, (g & 1) ? q2[0][3] + q2[1][3] : q2[0][2] + q2[1][2], srcl);
      const float mean0 = (s[0][0] + s[1][0]) * (1.0f / DM), mean1 = (s[0][2] + s[1][2]) * (1.0f / DM);
      const float var0 = fmaxf(ssq0 * (1.0f / DM) - mean0 * mean0, 0.f);
      const float var1 = fmaxf(ssq1 * (1.0f / DM) - mean1 * mean1, 0.f);
      uint32_t m0, m1;
      ln_params(mean0, var0, m0, r0);
      ln_params(mean1, var1, m1, r1);
#pragma unroll
      for (int k = 0; k < 32; ++k) {
        a[k][0] = hsub2_bf16(a[k][0], m0);
        a[k][1] = hsub2_bf16(a[k][1], m1);
        a[k][2] = hsub2_bf16(a[k][2], m0);
        a[k][3] = hsub2_bf16(a[k][3], m1);
      }
      XSTAMP(5);
      {
        uint4* dst = g_wgu + (size_t)(((b & 7) * 24 + ((b >> 3) & 7)) * 2 + (b >> 6)) * 512;
        const int nch = ((b & 7) == 7) ? 18 : 22;
#pragma unroll
        for (int u = 0; u < 6; ++u) {
          const int idx = u * 256 + tid;
          const int r = idx / 22, cc = idx - r * 22;
          if (idx < 1408 && cc < nch) dst[(cc >> 3) * 8 * 1024 + r * 8 + ((cc & 7) ^ (r & 7))] = rp[u];
        }
      }

      TSTAMP(1);
    }
    mbar_wait(bar_epoch, 0);
    const uint32_t epoch = *reinterpret_cast<volatile uint32_t*>(smem + SM_MISC);
    const uint32_t tag = epoch + 1;
    const int par = epoch & 1;
    const uint4* hhsrc = g_hh + slabB * 88 * 32 + lane;
    auto load_group = [&](int slot, int n) {
      const int p = n >> 2;
      const uint4* s = hhsrc + (11 * (((2 * n) & 7) + wg) + 4 * p) * 32;
#pragma unroll
      for (int ks = 0; ks < 4; ++ks) {
        if (ks < 3 || p < 2) {
          const uint4 v = ldg_cg(s + ks * 32);
          a[4 * slot + ks][0] = v.x; a[4 * slot + ks][1] = v.y; a[4 * slot + ks][2] = v.z; a[4 * slot + ks][3] = v.w;
        }
      }
    };
    auto wait_pass = [&](int p) { mbar_wait(bar_pass + p * 8, 0); };
    auto gemm_k512 = [&](float (&acc)[64], int n0, auto narrow, auto prep) {
      asm volatile("" : "+r"(n0));
      int st = n0 % NST, ph = (n0 / NST) & 1, prev = 0;
#pragma unroll
      for (int kt = 0; kt < 8; ++kt) {
        prep(kt);
        if ((kt & 3) == 0) order_wait();
        { ATTR_BEGIN(); mbar_wait(bar_full + st * 8, ph); ATTR_END(0); }
        wgmma_fence();
        const uint32_t d0 = dlo + st * (STAGE_BYTES >> 4);
#pragma unroll
        for (int ks = 0; ks < 4; ++ks) {
          const int k = 4 * kt + ks;
          if constexpr (decltype(narrow)::value)
            wgmma_rs_n112(*reinterpret_cast<float (*)[56]>(&acc[0]), a[k][0], a[k][1], a[k][2], a[k][3], make_desc(d0 + ks * 128), k > 0);
          else
            wgmma_rs_n128(acc, a[k][0], a[k][1], a[k][2], a[k][3], make_desc(d0 + ks * 128), k > 0);
        }
        wgmma_commit();
        if ((kt & 3) == 3 && !(decltype(narrow)::value && kt == 7 && wg == 1)) order_arrive();
        if (kt > 0) {
          wg_wait1();
          if (tw < 2) mbar_arrive_cluster(bar_empty + prev * 8, tw, 1);
          if constexpr (decltype(narrow)::value) {
            if (kt == 1) wait_pass(0);
            if (kt <= 4) load_group(kt - 1, kt - 1);
          }
        }
        prev = st;
        if (++st == NST) { st = 0; ph ^= 1; }
      }
      wgmma_wait<0>();
      if (tw < 2) mbar_arrive_cluster(bar_empty + prev * 8, tw, 1);

    };
    {
      float acc[64];
      gemm_k512(acc, N_KV, std::false_type{}, [](int) {});
      TSTAMP(2);
      ATTR_FLUSH(0);
      {
        const int mrow = w * 16 + ((lane >> 3) & 1) * 8 + (lane & 7);
        const int mch = lane >> 4;
#pragma unroll
        for (int hh = 0; hh < 4; ++hh) {
          const uint32_t off = mrow * 128 + (((2 * hh + mch) ^ (mrow & 7)) << 4);
          stmatrix_x4(stage + off, phi_pack(acc[8 * hh + 0] * r0, acc[8 * hh + 1] * r0), phi_pack(acc[8 * hh + 2] * r1, acc[8 * hh + 3] * r1),
                      phi_pack(acc[8 * hh + 4] * r0, acc[8 * hh + 5] * r0), phi_pack(acc[8 * hh + 6] * r1, acc[8 * hh + 7] * r1));
          stmatrix_x4(stage + 8192 + off, pack_bf16(acc[32 + 8 * hh + 0] * r0, acc[32 + 8 * hh + 1] * r0),
                      pack_bf16(acc[32 + 8 * hh + 2] * r1, acc[32 + 8 * hh + 3] * r1),
                      pack_bf16(acc[32 + 8 * hh + 4] * r0, acc[32 + 8 * hh + 5] * r0),
                      pack_bf16(acc[32 + 8 * hh + 6] * r1, acc[32 + 8 * hh + 7] * r1));
        }
      }
      named_bar(1 + wg);
    }
    {
      constexpr uint32_t ONES = 0x3F803F80u;
      float d0[4] = {}, d1[4] = {}, z0[4] = {}, z1[4] = {};
#pragma unroll
      for (int ks = 0; ks < 4; ++ks) {
        uint32_t va0, va1, va2, va3, pb0, pb1, pb2, pb3;
        {
          const int r = 16 * ks + (lane >> 4) * 8 + (lane & 7);
          const int ch = 2 * w + ((lane >> 3) & 1);
          ldmatrix_x4_trans(stage + 8192 + r * 128 + ((ch ^ (r & 7)) << 4), va0, va1, va2, va3);
        }
        {
          const int r = 16 * ks + ((lane >> 3) & 1) * 8 + (lane & 7);
          const int ch = 2 * w + (lane >> 4);
          ldmatrix_x4_trans(stage + r * 128 + ((ch ^ (r & 7)) << 4), pb0, pb1, pb2, pb3);
        }
        mma16816(d0, va0, va1, va2, va3, pb0, pb1);
        mma16816(d1, va0, va1, va2, va3, pb2, pb3);
        mma16816(z0, ONES, ONES, ONES, ONES, pb0, pb1);
        mma16816(z1, ONES, ONES, ONES, ONES, pb2, pb3);
      }
      const int head = 4 * tj1 + w;
      float4* kvp = &g_kv[par][(head * 32 + lane) * 2];
      red_add_v4(kvp, d0[0], d0[1], d1[0], d1[1]);
      red_add_v4(kvp + 1, d0[2], d0[3], d1[2], d1[3]);
      if (g == 0) red_add_v4(&g_z[par][head * 4 + t], z0[0], z0[1], z1[0], z1[1]);
      asm volatile("fence.proxy.async.global;" ::: "memory");
      publish(0);
      TSTAMP(3);
    }
    {
      uint32_t pq[4][4];
      {
        float accq[32];
        order_wait();
#pragma unroll
        for (int kt = 0; kt < 8; ++kt) {
          if ((kt & 1) == 0) wait_stage(N_Q + (kt >> 1));
          wgmma_fence();
#pragma unroll
          for (int ks = 0; ks < 4; ++ks) {
            const int k = 4 * kt + ks;
            wgmma_rs_n64(accq, a[k][0], a[k][1], a[k][2], a[k][3], desc_at(N_Q + (kt >> 1), (kt & 1) * 8192 + ks * 2048), k > 0);
          }
          wgmma_commit();
          if (kt == 7) order_arrive();
          if (kt > 0) {
            wg_wait1();
            if ((kt & 1) == 0) rel_stage(N_Q + (kt >> 1) - 1, 1);
          }
        }
        wgmma_wait<0>();
        rel_stage(N_Q + 3, 1);
        TSTAMP(4);
        ATTR_FLUSH(1);
#pragma unroll
        for (int hh = 0; hh < 4; ++hh) {
          pq[hh][0] = phi_pack(accq[8 * hh + 0] * r0, accq[8 * hh + 1] * r0);
          pq[hh][1] = phi_pack(accq[8 * hh + 2] * r1, accq[8 * hh + 3] * r1);
          pq[hh][2] = phi_pack(accq[8 * hh + 4] * r0, accq[8 * hh + 5] * r0);
          pq[hh][3] = phi_pack(accq[8 * hh + 6] * r1, accq[8 * hh + 7] * r1);
        }
      }
      if (b < 32) {
        g_kv[par ^ 1][b * 64 + (tid & 63)] = make_float4(0.f, 0.f, 0.f, 0.f);
        if (tid < 4) g_z[par ^ 1][b * 4 + tid] = make_float4(0.f, 0.f, 0.f, 0.f);
      }
      TSTAMP(5);
      mbar_wait(bar_kv, 0);
      if (b == 0 && tid == 0) asm volatile("st.relaxed.gpu.global.u32 [%0], %1;" ::"l"(&g_epoch), "r"(tag) : "memory");
      TSTAMP(6);
#pragma unroll
      for (int hh = 0; hh < 4; ++hh) {
        const int head = 4 * tj1 + hh;
        const uint4 kf = *reinterpret_cast<const uint4*>(smem + SM_KVF + hh * 544 + lane * 16);
        const uint2 zf = *reinterpret_cast<const uint2*>(smem + SM_KVF + hh * 544 + 512 + t * 8);
        float n0[4] = {}, n1[4] = {}, dn[4] = {};
        mma16816(dn, pq[hh][0], pq[hh][1], pq[hh][2], pq[hh][3], zf.x, zf.y);
        mma16816(n0, pq[hh][0], pq[hh][1], pq[hh][2], pq[hh][3], kf.x, kf.y);
        mma16816(n1, pq[hh][0], pq[hh][1], pq[hh][2], pq[hh][3], kf.z, kf.w);
        const float i0 = rcp_approx(dn[0] + 1e-6f), i1 = rcp_approx(dn[2] + 1e-6f);
        st_x(g_o + (slab1 * 32 + head) * 32 + lane, pack_bf16(n0[0] * i0, n0[1] * i0), pack_bf16(n0[2] * i1, n0[3] * i1),
             pack_bf16(n1[0] * i0, n1[1] * i0), pack_bf16(n1[2] * i1, n1[3] * i1));
      }
      TSTAMP(7);
    }

    auto cross_reduce = [&](float (&acc)[64], float (&out)[32]) {
      float4* mine = reinterpret_cast<float4*>(smem + SM_STAGE + wg * 16384) + tw;
      const float4* theirs = reinterpret_cast<const float4*>(smem + SM_STAGE + (wg ^ 1) * 16384) + tw;
#pragma unroll
      for (int i = 0; i < 8; ++i)
        mine[i * 128] = wg ? make_float4(acc[4 * i], acc[4 * i + 1], acc[4 * i + 2], acc[4 * i + 3])
                           : make_float4(acc[32 + 4 * i], acc[32 + 4 * i + 1], acc[32 + 4 * i + 2], acc[32 + 4 * i + 3]);
      asm volatile("bar.sync 4, 256;" ::: "memory");
#pragma unroll
      for (int i = 0; i < 8; ++i) {
        const float4 v = theirs[i * 128];
        out[4 * i + 0] = (wg ? acc[32 + 4 * i + 0] : acc[4 * i + 0]) + v.x;
        out[4 * i + 1] = (wg ? acc[32 + 4 * i + 1] : acc[4 * i + 1]) + v.y;
        out[4 * i + 2] = (wg ? acc[32 + 4 * i + 2] : acc[4 * i + 2]) + v.z;
        out[4 * i + 3] = (wg ? acc[32 + 4 * i + 3] : acc[4 * i + 3]) + v.w;
      }
    };

    {
      uint32_t xr[4][4];
#pragma unroll
      for (int q = 0; q < 4; ++q) {
        const uint32_t* p0 = reinterpret_cast<const uint32_t*>(prm.x + (size_t)rowB * DM + 64 * tjB + 16 * q + 2 * t);
        xr[q][0] = __ldg(p0);
        xr[q][1] = __ldg(p0 + 8 * DM / 2);
        xr[q][2] = __ldg(p0 + 4);
        xr[q][3] = __ldg(p0 + 8 * DM / 2 + 4);
      }
      const uint4* osrc = g_o + (slabB * 32 + 16 * wg) * 32;
      uint4 of[16];
      poll_sources(osrc, 4, 3, lane);
      fetch<16>(of, osrc + lane);
      float acc[64];
#pragma unroll
      for (int n = 0; n < 4; ++n) {
        const int sn = N_WO + 2 * n + wg;
        { ATTR_BEGIN(); ensure<4>(&of[4 * n], osrc + lane + 4 * n * 32); ATTR_END(1); }
        wait_stage(sn);
        wgmma_fence();
#pragma unroll
        for (int ks = 0; ks < 4; ++ks)
          wgmma_rs_n128(acc, of[4 * n + ks].x, of[4 * n + ks].y, of[4 * n + ks].z, of[4 * n + ks].w, desc_at(sn, ks * 2048), (n | ks) > 0);
        wgmma_commit();
        if (n > 0) {
          wg_wait1();
          rel_stage(sn - 2, 2);
        }
      }
      wgmma_wait<0>();
      rel_stage(N_WO + 6 + wg, 2);
      TSTAMP(8);
      ATTR_FLUSH(2);
      float sum[32];
      cross_reduce(acc, sum);

      uint32_t hf[4][4];
      float s0 = 0.f, s1 = 0.f;
#pragma unroll
      for (int q = 0; q < 4; ++q) {
#pragma unroll
        for (int r = 0; r < 4; ++r) {
          hf[q][r] = hadd2_bf16(xr[q][r], pack_bf16(sum[8 * q + 2 * r], sum[8 * q + 2 * r + 1]));
          const float sv = bf_lo(hf[q][r]) + bf_hi(hf[q][r]);
          if (r & 1) s1 += sv; else s0 += sv;
        }
        st_x(g_h + (slabB * 32 + 4 * tjB + q) * 32 + lane, hf[q][0], hf[q][1], hf[q][2], hf[q][3]);
      }
      s0 += __shfl_xor_sync(0xffffffffu, s0, 1); s1 += __shfl_xor_sync(0xffffffffu, s1, 1);
      s0 += __shfl_xor_sync(0xffffffffu, s0, 2); s1 += __shfl_xor_sync(0xffffffffu, s1, 2);
      const float mu0 = s0 * (1.0f / 64), mu1 = s1 * (1.0f / 64);
      float e0 = 0.f, e1 = 0.f;
#pragma unroll
      for (int q = 0; q < 4; ++q) {
#pragma unroll
        for (int r = 0; r < 4; ++r) {
          const float mu = (r & 1) ? mu1 : mu0;
          const float dl = bf_lo(hf[q][r]) - mu, dh = bf_hi(hf[q][r]) - mu;
          const float sv = dl * dl + dh * dh;
          if (r & 1) e1 += sv; else e0 += sv;
        }
      }
      e0 += __shfl_xor_sync(0xffffffffu, e0, 1); e1 += __shfl_xor_sync(0xffffffffu, e1, 1);
      e0 += __shfl_xor_sync(0xffffffffu, e0, 2); e1 += __shfl_xor_sync(0xffffffffu, e1, 2);
      if (t < 2) {
        const uint64_t pk = t == 0 ? ((uint64_t)__float_as_uint(e0) << 32 | __float_as_uint(mu0)) : ((uint64_t)__float_as_uint(e1) << 32 | __float_as_uint(mu1));
        const uint64_t* dst = reinterpret_cast<const uint64_t*>(g_hstat) + (rowB + 8 * t) * 8 + tjB;
        asm volatile("st.relaxed.gpu.global.u64 [%0], %1;" ::"l"(dst), "l"(pk) : "memory");
      }
      TSTAMP(9);
    }

    {
      const uint4* hsrc = g_h + slabA * 32 * 32;
      uint32_t m0, m1;
      {
#pragma unroll 1
        for (int it = 0; it < SPIN_LIMIT; ++it) {
          const uint4 q = ld_x(&g_hstat[slabA * 64 + t]);
          if (!__any_sync(0xffffffffu, q.x == POISON || q.z == POISON)) break;
        }
        uint4 p0 = ld_x(&g_hstat[rowA * 4 + t]), p1 = ld_x(&g_hstat[(rowA + 8) * 4 + t]);
#pragma unroll
        for (int k = 0; k < 32; ++k) {
          const uint4 v = ld_x(hsrc + lane + k * 32);
          a[k][0] = v.x; a[k][1] = v.y; a[k][2] = v.z; a[k][3] = v.w;
        }
#pragma unroll 1
        for (int it = 0; it < SPIN_LIMIT; ++it) {
          if (!__any_sync(0xffffffffu, p0.x == POISON || p0.z == POISON || p1.x == POISON || p1.z == POISON)) break;
          p0 = ld_x(&g_hstat[rowA * 4 + t]);
          p1 = ld_x(&g_hstat[(rowA + 8) * 4 + t]);
        }
        TSTAMP(10);
        const float a0x = __uint_as_float(p0.x), a0y = __uint_as_float(p0.y), a0z = __uint_as_float(p0.z), a0w = __uint_as_float(p0.w);
        const float a1x = __uint_as_float(p1.x), a1y = __uint_as_float(p1.y), a1z = __uint_as_float(p1.z), a1w = __uint_as_float(p1.w);
        float a0 = a0x + a0z, a1 = a1x + a1z;
        a0 += __shfl_xor_sync(0xffffffffu, a0, 1); a1 += __shfl_xor_sync(0xffffffffu, a1, 1);
        a0 += __shfl_xor_sync(0xffffffffu, a0, 2); a1 += __shfl_xor_sync(0xffffffffu, a1, 2);
        const float mean0 = a0 * 0.125f, mean1 = a1 * 0.125f;
        float v0 = a0y + a0w + 64.f * ((a0x - mean0) * (a0x - mean0) + (a0z - mean0) * (a0z - mean0));
        float v1 = a1y + a1w + 64.f * ((a1x - mean1) * (a1x - mean1) + (a1z - mean1) * (a1z - mean1));
        v0 += __shfl_xor_sync(0xffffffffu, v0, 1); v1 += __shfl_xor_sync(0xffffffffu, v1, 1);
        v0 += __shfl_xor_sync(0xffffffffu, v0, 2); v1 += __shfl_xor_sync(0xffffffffu, v1, 2);
        ln_params(mean0, v0 * (1.0f / DM), m0, r0);
        ln_params(mean1, v1 * (1.0f / DM), m1, r1);
      }
      auto prep_h = [&](int kt) {
        ATTR_BEGIN();
        if (__builtin_expect(__any_sync(0xffffffffu, a[4 * kt][0] == POISON || a[4 * kt + 1][0] == POISON || a[4 * kt + 2][0] == POISON || a[4 * kt + 3][0] == POISON), 0)) {
#pragma unroll 1
          for (int it = 0; it < SPIN_LIMIT; ++it) {
            uint4 v[4];
            fetch<4>(v, hsrc + lane + 4 * kt * 32);
#pragma unroll
            for (int ks = 0; ks < 4; ++ks) { a[4 * kt + ks][0] = v[ks].x; a[4 * kt + ks][1] = v[ks].y; a[4 * kt + ks][2] = v[ks].z; a[4 * kt + ks][3] = v[ks].w; }
            if (!any_poison<4>(v)) break;
          }
        }
        ATTR_END(1);
#pragma unroll
        for (int ks = 0; ks < 4; ++ks) {
          a[4 * kt + ks][0] = hsub2_bf16(a[4 * kt + ks][0], m0);
          a[4 * kt + ks][1] = hsub2_bf16(a[4 * kt + ks][1], m1);
          a[4 * kt + ks][2] = hsub2_bf16(a[4 * kt + ks][2], m0);
          a[4 * kt + ks][3] = hsub2_bf16(a[4 * kt + ks][3], m1);
        }
      };
#pragma unroll 1
      for (int p = 0; p < 3; ++p) {
        float acc[64];
        if (p == 0) gemm_k512(acc, N_GU + 8 * p, std::false_type{}, prep_h);
        else if (p == 1) gemm_k512(acc, N_GU + 8 * p, std::false_type{}, [](int) {});
        else gemm_k512(acc, N_GU + 8 * p, std::true_type{}, [](int) {});
#pragma unroll
        for (int qq = 0; qq < 4; ++qq) {
          if (qq < 3 || p < 2) {
            uint32_t v[4];
#pragma unroll
            for (int r = 0; r < 4; ++r) {
              const float sc = (r & 1) ? r1 : r0;
              v[r] = hmul2_bf16(pack_bf16(acc[8 * qq + 2 * r] * sc, acc[8 * qq + 2 * r + 1] * sc),
                                pack_bf16(acc[32 + 8 * qq + 2 * r] * sc, acc[32 + 8 * qq + 2 * r + 1] * sc));
            }
            g_hh[(slabA * 88 + 11 * tjA + 4 * p + qq) * 32 + lane] = make_uint4(v[0], v[1], v[2], v[3]);
          }
        }
        publish(1 + p);
      }
      TSTAMP(11);
      ATTR_FLUSH(3);
      TSTAMP(12);
    }

    {
      wait_pass(1);
#pragma unroll
      for (int n = 4; n < 8; ++n) load_group(n, n);
      TSTAMP(13);
      float acc[64];
#pragma unroll
      for (int n = 0; n < 12; ++n) {
        const int sn = N_DN + 2 * n + wg;
        const int sl = n & 7;
        if (n == 4) { ATTR_BEGIN(); wait_pass(2); ATTR_END(1); }
        wait_stage(sn);
        wgmma_fence();
#pragma unroll
        for (int ks = 0; ks < 4; ++ks)
          if (ks < 3 || n < 8)
            wgmma_rs_n128(acc, a[4 * sl + ks][0], a[4 * sl + ks][1], a[4 * sl + ks][2], a[4 * sl + ks][3], desc_at(sn, ks * 2048), (n | ks) > 0);
        wgmma_commit();
        if (n > 0) {
          wg_wait1();
          if (sn - 2 + NST < NSTAGES) rel_stage(sn - 2, 2);
          if (n >= 4 && n < 8) load_group(n - 4, n + 4);
        }
      }
      uint4 hf[4];
#pragma unroll
      for (int q = 0; q < 4; ++q) hf[q] = g_h[(slabB * 32 + 4 * tjB + q) * 32 + lane];
      wgmma_wait<0>();
      TSTAMP(14);
      ATTR_FLUSH(4);
      float sum[32];
      cross_reduce(acc, sum);
      asm volatile("bar.sync 4, 256;" ::: "memory");
      const uint32_t wst = stage + w * 2048;
      {
        const int mrow = ((lane >> 3) & 1) * 8 + (lane & 7);
        const int mch = lane >> 4;
#pragma unroll
        for (int q = 0; q < 4; ++q) {
          stmatrix_x4(wst + mrow * 128 + (((2 * q + mch) ^ (mrow & 7)) << 4),
                      hadd2_bf16(hf[q].x, pack_bf16(sum[8 * q + 0], sum[8 * q + 1])), hadd2_bf16(hf[q].y, pack_bf16(sum[8 * q + 2], sum[8 * q + 3])),
                      hadd2_bf16(hf[q].z, pack_bf16(sum[8 * q + 4], sum[8 * q + 5])), hadd2_bf16(hf[q].w, pack_bf16(sum[8 * q + 6], sum[8 * q + 7])));
        }
      }
      __syncwarp();
#pragma unroll
      for (int it = 0; it < 4; ++it) {
        const int r = it * 4 + (lane >> 3), ch = lane & 7;
        uint4 v;
        asm volatile("ld.shared.v4.u32 {%0,%1,%2,%3}, [%4];" : "=r"(v.x), "=r"(v.y), "=r"(v.z), "=r"(v.w) : "r"(wst + r * 128 + ((ch ^ (r & 7)) << 4)));
        *reinterpret_cast<uint4*>(prm.out + (size_t)(slabB * 16 + r) * DM + 64 * tjB + ch * 8) = v;
      }
      TSTAMP(15);
    }
  }
  asm volatile("barrier.cluster.arrive.relaxed.aligned;\nbarrier.cluster.wait.aligned;" ::: "memory");
}

typedef CUresult (*EncodeTiledFn)(CUtensorMap*, CUtensorMapDataType, cuuint32_t, void*, const cuuint64_t*, const cuuint64_t*,
                                  const cuuint32_t*, const cuuint32_t*, CUtensorMapInterleave, CUtensorMapSwizzle,
                                  CUtensorMapL2promotion, CUtensorMapFloatOOBfill);

void encode_blk(EncodeTiledFn enc, CUtensorMap* tm, const void* p, int rows, int cols, int box_rows, int box_blks) {
  cuuint64_t gd[3] = {64, (cuuint64_t)rows, (cuuint64_t)cols / 64};
  cuuint64_t gs[2] = {(cuuint64_t)cols * 2, 128};
  cuuint32_t bx[3] = {64, (cuuint32_t)box_rows, (cuuint32_t)box_blks};
  cuuint32_t es[3] = {1, 1, 1};
  enc(tm, CU_TENSOR_MAP_DATA_TYPE_BFLOAT16, 3, const_cast<void*>(p), gd, gs, bx, es, CU_TENSOR_MAP_INTERLEAVE_NONE,
      CU_TENSOR_MAP_SWIZZLE_128B, CU_TENSOR_MAP_L2_PROMOTION_L2_128B, CU_TENSOR_MAP_FLOAT_OOB_FILL_NONE);
}

}

extern "C" void kernel_launch(void* const* d_in, const int* in_sizes, int n_in, void* d_out, int out_size) {
  (void)in_sizes; (void)n_in; (void)out_size;
  static CUtensorMap tm_x, tm_qkv, tm_wo, tm_down64, tm_down48;
  static const void* cached[4] = {nullptr, nullptr, nullptr, nullptr};
  static bool attr_done = false;
  const void* ptrs[4] = {d_in[1], d_in[2], d_in[6], d_in[0]};
  bool same = true;
  for (int i = 0; i < 4; ++i) same = same && (cached[i] == ptrs[i]);
  if (!same) {
    void* fn = nullptr;
    cudaDriverEntryPointQueryResult qr;
    cudaGetDriverEntryPoint("cuTensorMapEncodeTiled", &fn, cudaEnableDefault, &qr);
    EncodeTiledFn enc = (EncodeTiledFn)fn;
    encode_blk(enc, &tm_qkv, ptrs[0], DM, 3 * DM, 64, 1);
    encode_blk(enc, &tm_wo, ptrs[1], DM, DM, 64, 2);
    encode_blk(enc, &tm_down64, ptrs[2], FF, DM, 64, 2);
    encode_blk(enc, &tm_down48, ptrs[2], FF, DM, 48, 1);
    encode_blk(enc, &tm_x, ptrs[3], 2048, DM, 64, 2);
    for (int i = 0; i < 4; ++i) cached[i] = ptrs[i];
  }
  if (!attr_done) {
    cudaFuncSetAttribute(fused_block_kernel, cudaFuncAttributeMaxDynamicSharedMemorySize, SM_TOTAL);
    attr_done = true;
  }
  Params prm;
  prm.x = (const __nv_bfloat16*)d_in[0];
  prm.w_gate = (const __nv_bfloat16*)d_in[4];
  prm.w_up = (const __nv_bfloat16*)d_in[5];
  prm.out = (__nv_bfloat16*)d_out;
  cudaLaunchConfig_t cfg = {};
  cfg.gridDim = dim3(NCTA);
  cfg.blockDim = dim3(384);
  cfg.dynamicSmemBytes = SM_TOTAL;
  cfg.stream = cudaStreamPerThread;
  cudaLaunchAttribute at[1];
  at[0].id = cudaLaunchAttributeClusterDimension;
  at[0].val.clusterDim.x = 2;
  at[0].val.clusterDim.y = 1;
  at[0].val.clusterDim.z = 1;
  cfg.attrs = at;
  cfg.numAttrs = 1;
  cudaLaunchKernelEx(&cfg, fused_block_kernel, tm_x, tm_qkv, tm_wo, tm_down64, tm_down48, prm);
}
```

```cpp
#include <cuda_runtime.h>
#include <cuda_bf16.h>
#include <cuda.h>
#include <stdint.h>
#include <type_traits>

namespace {

constexpr int DM = 512;
constexpr int FF = 1376;
constexpr int NCTA = 128;
constexpr int NST = 12;
constexpr int STAGE_BYTES = 16384;
constexpr int N_X = 0, N_KV = 8, N_Q = 16, N_WO = 20, N_GU = 28, N_DN = 52, NSTAGES = 76;

constexpr int SM_STAGE = NST * STAGE_BYTES;
constexpr int SM_BAR = SM_STAGE + 32768;
constexpr int SM_EBAR = SM_BAR + 2 * NST * 8;
constexpr int SM_KBAR = SM_EBAR + 8;
constexpr int SM_PBAR = SM_KBAR + 8;
constexpr int SM_UBAR = SM_PBAR + 24;
constexpr int SM_MISC = SM_UBAR + 64;
constexpr int SM_TOTAL = SM_MISC + 16;

constexpr int SPIN_LIMIT = 1 << 18;
constexpr uint32_t POISON = 0xFFFFFFFFu;

__device__ uint4 g_pq[2][128 * 32 * 32];
__device__ uint4 g_h[128 * 32 * 32];
__device__ uint4 g_hh[128 * 88 * 32];
__device__ uint4 g_hstat[2048 * 4];
__device__ float4 g_kv[2][32 * 32 * 2];
__device__ float4 g_z[2][32 * 4];
__device__ uint4 g_wgu[8 * 3 * 8 * 2 * 512];
__device__ uint32_t g_hhflag[32 * 3 * 8];
__device__ uint32_t g_kvcnt[8 * 32];
__device__ uint32_t g_epoch;

__device__ __forceinline__ uint32_t smem_u32(const void* p) { return (uint32_t)__cvta_generic_to_shared(p); }
__device__ __forceinline__ void mbar_init(uint32_t bar, uint32_t cnt) {
  asm volatile("mbarrier.init.shared::cta.b64 [%0], %1;" ::"r"(bar), "r"(cnt) : "memory");
}
__device__ __forceinline__ void mbar_expect_tx(uint32_t bar, uint32_t bytes) {
  asm volatile("mbarrier.arrive.expect_tx.shared::cta.b64 _, [%0], %1;" ::"r"(bar), "r"(bytes) : "memory");
}
__device__ __forceinline__ void mbar_arrive(uint32_t bar) {
  asm volatile("mbarrier.arrive.shared::cta.b64 _, [%0];" ::"r"(bar) : "memory");
}
__device__ __forceinline__ void mbar_wait(uint32_t bar, uint32_t parity) {
  asm volatile(
      "{\n.reg .pred p;\n.reg .u32 c;\nmov.u32 c, 0;\n"
      "W%=:\nmbarrier.try_wait.parity.shared::cta.b64 p, [%0], %1;\n@p bra D%=;\n"
      "add.u32 c, c, 1;\nsetp.lt.u32 p, c, %2;\n@p bra W%=;\nD%=:\n}\n" ::"r"(bar), "r"(parity), "n"(SPIN_LIMIT)
      : "memory");
}
__device__ __forceinline__ void tma_3d_mc(uint32_t dst, const CUtensorMap* tm, uint32_t bar, int c1, int c2) {
  asm volatile(
      "cp.async.bulk.tensor.3d.shared::cluster.global.mbarrier::complete_tx::bytes.multicast::cluster [%0], [%1, {%3, %4, %5}], [%2], %6;" ::"r"(dst),
      "l"((uint64_t)tm), "r"(bar), "r"(0), "r"(c1), "r"(c2), "h"((uint16_t)3)
      : "memory");
}
__device__ __forceinline__ void tma_3d(uint32_t dst, const CUtensorMap* tm, uint32_t bar, int c1, int c2) {
  asm volatile(
      "cp.async.bulk.tensor.3d.shared::cluster.global.mbarrier::complete_tx::bytes [%0], [%1, {%3, %4, %5}], [%2];" ::"r"(dst),
      "l"((uint64_t)tm), "r"(bar), "r"(0), "r"(c1), "r"(c2)
      : "memory");
}
__device__ __forceinline__ void bulk_g2s_mc(uint32_t dst, const void* src, uint32_t bytes, uint32_t bar) {
  asm volatile("cp.async.bulk.shared::cluster.global.mbarrier::complete_tx::bytes.multicast::cluster [%0], [%1], %2, [%3], %4;" ::"r"(dst),
               "l"(src), "r"(bytes), "r"(bar), "h"((uint16_t)3)
               : "memory");
}
__device__ __forceinline__ void mbar_arrive_cluster(uint32_t bar, uint32_t rank, uint32_t count) {
  asm volatile(
      "{\n.reg .b32 ra;\nmapa.shared::cluster.u32 ra, %0, %1;\nmbarrier.arrive.shared::cluster.b64 _, [ra], %2;\n}\n" ::"r"(bar), "r"(rank), "r"(count)
      : "memory");
}
__device__ __forceinline__ void wgmma_fence() { asm volatile("wgmma.fence.sync.aligned;" ::: "memory"); }
__device__ __forceinline__ void wgmma_commit() { asm volatile("wgmma.commit_group.sync.aligned;" ::: "memory"); }
template <int N>
__device__ __forceinline__ void wgmma_wait() { asm volatile("wgmma.wait_group.sync.aligned %0;" ::"n"(N) : "memory"); }

__device__ __forceinline__ uint64_t make_desc(uint32_t lo) {
  return (uint64_t)lo | ((uint64_t)((1024u >> 4) | (1u << 30)) << 32);
}

__device__ __forceinline__ void wgmma_rs_n64(float (&d)[32], uint32_t a0, uint32_t a1, uint32_t a2, uint32_t a3, uint64_t descB, int scaleD) {
  asm volatile(
    "{\n.reg .pred p;\nsetp.ne.b32 p, %37, 0;\n"
    "wgmma.mma_async.sync.aligned.m64n64k16.f32.bf16.bf16 "
    "{%0, %1, %2, %3, %4, %5, %6, %7, %8, %9, %10, %11, %12, %13, %14, %15, "
    "%16, %17, %18, %19, %20, %21, %22, %23, %24, %25, %26, %27, %28, %29, %30, %31}, "
    "{%32, %33, %34, %35}, %36, p, 1, 1, 1;\n}\n"
    : "+f"(d[0]), "+f"(d[1]), "+f"(d[2]), "+f"(d[3]), "+f"(d[4]), "+f"(d[5]), "+f"(d[6]), "+f"(d[7]),
      "+f"(d[8]), "+f"(d[9]), "+f"(d[10]), "+f"(d[11]), "+f"(d[12]), "+f"(d[13]), "+f"(d[14]), "+f"(d[15]),
      "+f"(d[16]), "+f"(d[17]), "+f"(d[18]), "+f"(d[19]), "+f"(d[20]), "+f"(d[21]), "+f"(d[22]), "+f"(d[23]),
      "+f"(d[24]), "+f"(d[25]), "+f"(d[26]), "+f"(d[27]), "+f"(d[28]), "+f"(d[29]), "+f"(d[30]), "+f"(d[31])
    : "r"(a0), "r"(a1), "r"(a2), "r"(a3), "l"(descB), "r"(scaleD));
}

__device__ __forceinline__ void wgmma_rs_n112(float (&d)[56], uint32_t a0, uint32_t a1, uint32_t a2, uint32_t a3, uint64_t descB, int scaleD) {
  asm volatile(
    "{\n.reg .pred p;\nsetp.ne.b32 p, %61, 0;\n"
    "wgmma.mma_async.sync.aligned.m64n112k16.f32.bf16.bf16 "
    "{%0, %1, %2, %3, %4, %5, %6, %7, %8, %9, %10, %11, %12, %13, %14, %15, "
    "%16, %17, %18, %19, %20, %21, %22, %23, %24, %25, %26, %27, %28, %29, %30, %31, "
    "%32, %33, %34, %35, %36, %37, %38, %39, %40, %41, %42, %43, %44, %45, %46, %47, "
    "%48, %49, %50, %51, %52, %53, %54, %55}, "
    "{%56, %57, %58, %59}, %60, p, 1, 1, 1;\n}\n"
    : "+f"(d[0]), "+f"(d[1]), "+f"(d[2]), "+f"(d[3]), "+f"(d[4]), "+f"(d[5]), "+f"(d[6]), "+f"(d[7]),
      "+f"(d[8]), "+f"(d[9]), "+f"(d[10]), "+f"(d[11]), "+f"(d[12]), "+f"(d[13]), "+f"(d[14]), "+f"(d[15]),
      "+f"(d[16]), "+f"(d[17]), "+f"(d[18]), "+f"(d[19]), "+f"(d[20]), "+f"(d[21]), "+f"(d[22]), "+f"(d[23]),
      "+f"(d[24]), "+f"(d[25]), "+f"(d[26]), "+f"(d[27]), "+f"(d[28]), "+f"(d[29]), "+f"(d[30]), "+f"(d[31]),
      "+f"(d[32]), "+f"(d[33]), "+f"(d[34]), "+f"(d[35]), "+f"(d[36]), "+f"(d[37]), "+f"(d[38]), "+f"(d[39]),
      "+f"(d[40]), "+f"(d[41]), "+f"(d[42]), "+f"(d[43]), "+f"(d[44]), "+f"(d[45]), "+f"(d[46]), "+f"(d[47]),
      "+f"(d[48]), "+f"(d[49]), "+f"(d[50]), "+f"(d[51]), "+f"(d[52]), "+f"(d[53]), "+f"(d[54]), "+f"(d[55])
    : "r"(a0), "r"(a1), "r"(a2), "r"(a3), "l"(descB), "r"(scaleD));
}

__device__ __forceinline__ void wgmma_rs_n128(float (&d)[64], uint32_t a0, uint32_t a1, uint32_t a2, uint32_t a3, uint64_t descB, int scaleD) {
  asm volatile(
    "{\n.reg .pred p;\nsetp.ne.b32 p, %69, 0;\n"
    "wgmma.mma_async.sync.aligned.m64n128k16.f32.bf16.bf16 "
    "{%0, %1, %2, %3, %4, %5, %6, %7, %8, %9, %10, %11, %12, %13, %14, %15, "
    "%16, %17, %18, %19, %20, %21, %22, %23, %24, %25, %26, %27, %28, %29, %30, %31, "
    "%32, %33, %34, %35, %36, %37, %38, %39, %40, %41, %42, %43, %44, %45, %46, %47, "
    "%48, %49, %50, %51, %52, %53, %54, %55, %56, %57, %58, %59, %60, %61, %62, %63}, "
    "{%64, %65, %66, %67}, %68, p, 1, 1, 1;\n}\n"
    : "+f"(d[0]), "+f"(d[1]), "+f"(d[2]), "+f"(d[3]), "+f"(d[4]), "+f"(d[5]), "+f"(d[6]), "+f"(d[7]),
      "+f"(d[8]), "+f"(d[9]), "+f"(d[10]), "+f"(d[11]), "+f"(d[12]), "+f"(d[13]), "+f"(d[14]), "+f"(d[15]),
      "+f"(d[16]), "+f"(d[17]), "+f"(d[18]), "+f"(d[19]), "+f"(d[20]), "+f"(d[21]), "+f"(d[22]), "+f"(d[23]),
      "+f"(d[24]), "+f"(d[25]), "+f"(d[26]), "+f"(d[27]), "+f"(d[28]), "+f"(d[29]), "+f"(d[30]), "+f"(d[31]),
      "+f"(d[32]), "+f"(d[33]), "+f"(d[34]), "+f"(d[35]), "+f"(d[36]), "+f"(d[37]), "+f"(d[38]), "+f"(d[39]),
      "+f"(d[40]), "+f"(d[41]), "+f"(d[42]), "+f"(d[43]), "+f"(d[44]), "+f"(d[45]), "+f"(d[46]), "+f"(d[47]),
      "+f"(d[48]), "+f"(d[49]), "+f"(d[50]), "+f"(d[51]), "+f"(d[52]), "+f"(d[53]), "+f"(d[54]), "+f"(d[55]),
      "+f"(d[56]), "+f"(d[57]), "+f"(d[58]), "+f"(d[59]), "+f"(d[60]), "+f"(d[61]), "+f"(d[62]), "+f"(d[63])
    : "r"(a0), "r"(a1), "r"(a2), "r"(a3), "l"(descB), "r"(scaleD));
}


__device__ __forceinline__ void mma16816(float (&c)[4], uint32_t a0, uint32_t a1, uint32_t a2, uint32_t a3, uint32_t b0, uint32_t b1) {
  asm("mma.sync.aligned.m16n8k16.row.col.f32.bf16.bf16.f32 {%0,%1,%2,%3}, {%4,%5,%6,%7}, {%8,%9}, {%0,%1,%2,%3};"
      : "+f"(c[0]), "+f"(c[1]), "+f"(c[2]), "+f"(c[3])
      : "r"(a0), "r"(a1), "r"(a2), "r"(a3), "r"(b0), "r"(b1));
}
__device__ __forceinline__ void stmatrix_x4(uint32_t addr, uint32_t r0, uint32_t r1, uint32_t r2, uint32_t r3) {
  asm volatile("stmatrix.sync.aligned.m8n8.x4.shared.b16 [%0], {%1,%2,%3,%4};" ::"r"(addr), "r"(r0), "r"(r1), "r"(r2), "r"(r3) : "memory");
}
__device__ __forceinline__ void ldmatrix_x4(uint32_t addr, uint32_t& r0, uint32_t& r1, uint32_t& r2, uint32_t& r3) {
  asm volatile("ldmatrix.sync.aligned.m8n8.x4.shared.b16 {%0,%1,%2,%3}, [%4];"
               : "=r"(r0), "=r"(r1), "=r"(r2), "=r"(r3)
               : "r"(addr)
               : "memory");
}
__device__ __forceinline__ void ldmatrix_x4_trans(uint32_t addr, uint32_t& r0, uint32_t& r1, uint32_t& r2, uint32_t& r3) {
  asm volatile("ldmatrix.sync.aligned.m8n8.x4.trans.shared.b16 {%0,%1,%2,%3}, [%4];"
               : "=r"(r0), "=r"(r1), "=r"(r2), "=r"(r3)
               : "r"(addr)
               : "memory");
}
__device__ __forceinline__ uint32_t pack_bf16(float lo, float hi) {
  uint32_t r;
  asm("cvt.rn.bf16x2.f32 %0, %1, %2;" : "=r"(r) : "f"(hi), "f"(lo));
  return r;
}
__device__ __forceinline__ float bf_lo(uint32_t v) { return __uint_as_float(v << 16); }
__device__ __forceinline__ float bf_hi(uint32_t v) { return __uint_as_float(v & 0xffff0000u); }
__device__ __forceinline__ float bf16r(float x) { return bf_lo(pack_bf16(x, 0.f)); }
__device__ __forceinline__ uint32_t hsub2_bf16(uint32_t a, uint32_t b) {
  uint32_t r;
  asm("sub.rn.bf16x2 %0, %1, %2;" : "=r"(r) : "r"(a), "r"(b));
  return r;
}
__device__ __forceinline__ uint32_t hadd2_bf16(uint32_t a, uint32_t b) {
  uint32_t r;
  asm("add.rn.bf16x2 %0, %1, %2;" : "=r"(r) : "r"(a), "r"(b));
  return r;
}
__device__ __forceinline__ uint32_t hmul2_bf16(uint32_t a, uint32_t b) {
  uint32_t r;
  asm("mul.rn.bf16x2 %0, %1, %2;" : "=r"(r) : "r"(a), "r"(b));
  return r;
}
__device__ __forceinline__ void ln_params(float mean, float var, uint32_t& m2, float& rinv) {
  m2 = pack_bf16(mean, mean);
  const float ve = bf16r(bf16r(var) + 1e-5f);
  rinv = 1.0f / bf16r(sqrtf(ve));
}
__device__ __forceinline__ float ex2_approx(float x) {
  float r;
  asm("ex2.approx.ftz.f32 %0, %1;" : "=f"(r) : "f"(x));
  return r;
}
__device__ __forceinline__ float rcp_approx(float x) {
  float r;
  asm("rcp.approx.ftz.f32 %0, %1;" : "=f"(r) : "f"(x));
  return r;
}
__device__ __forceinline__ uint32_t phi_pack(float a, float b) {
  const uint32_t t = pack_bf16(a, b);
  const uint32_t lin = hadd2_bf16(t, 0x3F803F80u);
  const uint32_t ex = pack_bf16(ex2_approx(bf_lo(t) * 1.4426950408889634f), ex2_approx(bf_hi(t) * 1.4426950408889634f));
  uint32_t mask;
  asm("set.gt.u32.bf16x2 %0, %1, %2;" : "=r"(mask) : "r"(t), "r"(0u));
  const uint32_t p = (lin & mask) | (ex & ~mask);
  return hadd2_bf16(p, 0x35863586u);
}
__device__ __forceinline__ uint4 ldg_nc(const uint4* p) {
  uint4 v;
  asm volatile("ld.global.nc.L1::no_allocate.v4.u32 {%0,%1,%2,%3}, [%4];" : "=r"(v.x), "=r"(v.y), "=r"(v.z), "=r"(v.w) : "l"(p));
  return v;
}
__device__ __forceinline__ uint4 ldg_cg(const uint4* p) {
  uint4 v;
  asm volatile("ld.global.cg.v4.u32 {%0,%1,%2,%3}, [%4];" : "=r"(v.x), "=r"(v.y), "=r"(v.z), "=r"(v.w) : "l"(p) : "memory");
  return v;
}
__device__ __forceinline__ float4 ldg_cg_f4(const float4* p) {
  float4 v;
  asm volatile("ld.global.cg.v4.f32 {%0,%1,%2,%3}, [%4];" : "=f"(v.x), "=f"(v.y), "=f"(v.z), "=f"(v.w) : "l"(p) : "memory");
  return v;
}
__device__ __forceinline__ uint4 ld_x(const uint4* p) {
  uint4 v;
  asm volatile("{\n.reg .b128 q;\nld.relaxed.gpu.global.b128 q, [%4];\nmov.b128 {%0,%1,%2,%3}, q;\n}\n"
               : "=r"(v.x), "=r"(v.y), "=r"(v.z), "=r"(v.w)
               : "l"(p)
               : "memory");
  return v;
}
__device__ __forceinline__ void st_x(uint4* p, uint32_t a, uint32_t b, uint32_t c, uint32_t d) {
  asm volatile("{\n.reg .b128 q;\nmov.b128 q, {%1,%2,%3,%4};\nst.relaxed.gpu.global.b128 [%0], q;\n}\n" ::"l"(p), "r"(a), "r"(b), "r"(c), "r"(d)
               : "memory");
}
__device__ __forceinline__ uint32_t ld_acquire(const uint32_t* p) {
  uint32_t v;
  asm volatile("ld.acquire.gpu.global.u32 %0, [%1];" : "=r"(v) : "l"(p) : "memory");
  return v;
}
__device__ __forceinline__ void red_add_v4(float4* p, float a, float b, float c, float d) {
  asm volatile("red.relaxed.gpu.global.add.v4.f32 [%0], {%1,%2,%3,%4};" ::"l"(p), "f"(a), "f"(b), "f"(c), "f"(d) : "memory");
}
__device__ __forceinline__ void named_bar(int id) { asm volatile("bar.sync %0, 128;" ::"r"(id) : "memory"); }

template <int N>
__device__ __forceinline__ void fetch(uint4* r, const uint4* p) {
#pragma unroll
  for (int i = 0; i < N; ++i) r[i] = ld_x(p + i * 32);
}
template <int N, uint32_t SENT = POISON>
__device__ __forceinline__ bool any_poison(const uint4* r) {
  bool bad = false;
#pragma unroll
  for (int i = 0; i < N; ++i) bad |= (r[i].x == SENT);
  return __any_sync(0xffffffffu, bad);
}
template <int N, uint32_t SENT = POISON>
__device__ __forceinline__ void ensure(uint4* r, const uint4* p) {
  if (__builtin_expect((any_poison<N, SENT>(r)), 0)) {
#pragma unroll 1
    for (int it = 0; it < SPIN_LIMIT; ++it) {
      fetch<N>(r, p);
      if (!any_poison<N, SENT>(r)) break;
    }
  }
}

template <uint32_t SENT>
__device__ __forceinline__ void poll_sources(const uint4* base, int frags_per_src, int nsrc_mask, int lane) {
  const uint32_t* p = reinterpret_cast<const uint32_t*>(base + (((lane & nsrc_mask) + 1) * frags_per_src - 1) * 32 + 31);
  uint32_t v0, v1;
  asm volatile("ld.relaxed.gpu.global.u32 %0, [%1];" : "=r"(v0) : "l"(p) : "memory");
#pragma unroll 1
  for (int it = 0; it < SPIN_LIMIT; ++it) {
    asm volatile("ld.relaxed.gpu.global.u32 %0, [%1];" : "=r"(v1) : "l"(p) : "memory");
    if (!__any_sync(0xffffffffu, v0 == SENT)) break;
    asm volatile("ld.relaxed.gpu.global.u32 %0, [%1];" : "=r"(v0) : "l"(p) : "memory");
    if (!__any_sync(0xffffffffu, v1 == SENT)) break;
  }
}

struct Params {
  const __nv_bfloat16* x;
  const __nv_bfloat16* w_gate;
  const __nv_bfloat16* w_up;
  __nv_bfloat16* out;
};

__global__ void __launch_bounds__(384, 1)
fused_block_kernel(const __grid_constant__ CUtensorMap tm_x, const __grid_constant__ CUtensorMap tm_qkv, const __grid_constant__ CUtensorMap tm_wo,
                   const __grid_constant__ CUtensorMap tm_down64, const __grid_constant__ CUtensorMap tm_down48, const Params prm) {
  extern __shared__ __align__(1024) uint8_t smem[];
  const uint32_t sbase = smem_u32(smem);
  const int tid = threadIdx.x;
  const int warp = tid >> 5, lane = tid & 31;
  const int b = blockIdx.x;
  const int cm = b & 1, cp = b >> 1;
  int dom, pos;
  if (cp < 4) { dom = 15; pos = cp; }
  else if (cp < 36) { dom = (cp - 4) & 7; pos = (cp - 4) >> 3; }
  else { dom = 8 + (cp - 36) % 7; pos = (cp - 36) / 7; }
  const int ti1 = cp >> 2, tj1 = 2 * (cp & 3) + cm;
  const int tiA = 2 * (dom >> 1) + cm, tjA = (dom & 1) * 4 + pos;
  const int rtB = 2 * dom + cm, jjB = pos;
  const uint32_t bar_full = sbase + SM_BAR, bar_empty = sbase + SM_BAR + NST * 8;
  const uint32_t bar_epoch = sbase + SM_EBAR, bar_kv = sbase + SM_KBAR, bar_pass = sbase + SM_PBAR, bar_pub = sbase + SM_UBAR;

  if (tid == 256) {
    asm volatile("prefetch.tensormap [%0];" ::"l"((uint64_t)&tm_x) : "memory");
    asm volatile("prefetch.tensormap [%0];" ::"l"((uint64_t)&tm_qkv) : "memory");
    asm volatile("prefetch.tensormap [%0];" ::"l"((uint64_t)&tm_wo) : "memory");
    asm volatile("prefetch.tensormap [%0];" ::"l"((uint64_t)&tm_down64) : "memory");
    asm volatile("prefetch.tensormap [%0];" ::"l"((uint64_t)&tm_down48) : "memory");
  }
  if (tid == 0) {
    for (int s = 0; s < NST; ++s) {
      mbar_init(bar_full + s * 8, 1);
      mbar_init(bar_empty + s * 8, 4);
    }
    mbar_init(bar_epoch, 1);
    mbar_init(bar_kv, 1);
    for (int p = 0; p < 3; ++p) mbar_init(bar_pass + p * 8, 1);
    for (int p = 0; p < 8; ++p) mbar_init(bar_pub + p * 8, 4);
    asm volatile("fence.mbarrier_init.release.cluster;" ::: "memory");
  }
  __syncthreads();
  asm volatile("barrier.cluster.arrive.relaxed.aligned;" ::: "memory");

  if (warp >= 8) {
    asm volatile("setmaxnreg.dec.sync.aligned.u32 40;");
    const int pw = warp - 8;
    if (pw == 2 && lane == 0) {
      uint32_t e;
      asm volatile("ld.relaxed.gpu.global.u32 %0, [%1];" : "=r"(e) : "l"(&g_epoch) : "memory");
      *reinterpret_cast<volatile uint32_t*>(smem + SM_MISC) = e;
      mbar_arrive(bar_epoch);
    }
    asm volatile("barrier.cluster.wait.aligned;" ::: "memory");
    if (pw < 2) {
      if (lane == 0) {
        bool gu_ready = false;
#pragma unroll 1
        for (int n = pw; n < NSTAGES; n += 2) {
          const int st = n % NST;
          const uint32_t fb = bar_full + st * 8, dst = sbase + st * STAGE_BYTES;
          if (n >= NST) mbar_wait(bar_empty + st * 8, ((n / NST) - 1) & 1);
          if (n == N_KV + pw) mbar_wait(bar_full + (N_X + 4 + pw) * 8, 0);
          const bool short_tile = n >= N_DN + 16;
          mbar_expect_tx(fb, short_tile ? 12288 : STAGE_BYTES);
          if (n >= N_KV && n < N_WO) {
            if (n < N_Q) {
              tma_3d(dst, &tm_qkv, fb, 64 * (n - N_KV), 8 + tj1);
              tma_3d(dst + 8192, &tm_qkv, fb, 64 * (n - N_KV), 16 + tj1);
            } else {
              tma_3d(dst, &tm_qkv, fb, 128 * (n - N_Q), tj1);
              tma_3d(dst + 8192, &tm_qkv, fb, 128 * (n - N_Q) + 64, tj1);
            }
            continue;
          }
          if (pw != cm) continue;
          if (n < N_KV) {
            tma_3d_mc(dst, &tm_x, fb, (2 * ti1 + (n & 1)) * 64, 2 * (n >> 1));
          } else if (n < N_GU) {
            const int r = n - N_WO;
            tma_3d_mc(dst, &tm_wo, fb, 64 * ((r >> 1) + 4 * (r & 1)), 2 * jjB);
          } else if (n < N_DN) {
            if (!gu_ready) {
              mbar_wait(bar_kv, 0);
              asm volatile("fence.proxy.async.global;" ::: "memory");
              gu_ready = true;
            }
            bulk_g2s_mc(dst, g_wgu + (size_t)(tjA * 24 + (n - N_GU)) * 1024, STAGE_BYTES, fb);
          } else {
            const int u = n - N_DN;
            if (short_tile) {
              tma_3d_mc(dst, &tm_down48, fb, 176 * (u & 7) + 128, 2 * jjB);
              tma_3d_mc(dst + 8192, &tm_down48, fb, 176 * (u & 7) + 128, 2 * jjB + 1);
            } else {
              tma_3d_mc(dst, &tm_down64, fb, 176 * (u & 7) + 64 * (u >> 3), 2 * jjB);
            }
          }
        }
      }
      __syncwarp();
    } else {
      const int wg = pw - 2;
      mbar_wait(bar_epoch, 0);
      const uint32_t tag = *reinterpret_cast<volatile uint32_t*>(smem + SM_MISC) + 1;
      {
        const int tjB = 2 * jjB + wg;
#pragma unroll 1
        for (int w = 0; w < 4; ++w) {
          const int slab1 = (2 * ti1 + wg) * 4 + w, slabB = rtB * 4 + w;
#pragma unroll
          for (int q = 0; q < 4; ++q) {
            g_h[(slabB * 32 + 4 * tjB + q) * 32 + lane] = make_uint4(POISON, POISON, POISON, POISON);
            g_pq[tag & 1][(slab1 * 32 + 4 * tj1 + q) * 32 + lane] = make_uint4(0, 0, 0, 0);
          }
          if (lane < 16) reinterpret_cast<uint2*>(g_hstat)[(slabB * 16 + lane) * 8 + tjB] = make_uint2(POISON, POISON);
        }
      }
      asm volatile("bar.sync 9, 64;" ::: "memory");
      if (wg == 0) {
#pragma unroll 1
        for (int v = 0; v < 2; ++v) {
          mbar_wait(bar_pub + v * 8, 0);
          if (lane == 0) asm volatile("red.release.gpu.global.add.u32 [%0], 1;" ::"l"(&g_kvcnt[tj1 * 32]) : "memory");
        }
        const uint32_t target = 32u * tag;
#pragma unroll 1
        for (int it = 0; it < SPIN_LIMIT; ++it) {
          uint32_t v = target;
          if (lane < 8) v = ld_acquire(&g_kvcnt[lane * 32]);
          if (__all_sync(0xffffffffu, (int)(v - target) >= 0)) break;
        }
        __syncwarp();
        if (lane == 0) mbar_arrive(bar_kv);
#pragma unroll 1
        for (int pv = 0; pv < 6; ++pv) {
          const int p = pv >> 1, v = pv & 1;
          mbar_wait(bar_pub + (2 + pv) * 8, 0);
          if (lane == 0) asm volatile("st.release.gpu.global.u32 [%0], %1;" ::"l"(&g_hhflag[((2 * tiA + v) * 3 + p) * 8 + tjA]), "r"(tag) : "memory");
        }
      } else {
        mbar_wait(bar_kv, 0);
#pragma unroll 1
        for (int p = 0; p < 3; ++p) {
          const uint32_t* f = &g_hhflag[(rtB * 3 + p) * 8 + (lane & 7)];
#pragma unroll 1
          for (int it = 0; it < SPIN_LIMIT; ++it) {
            if (__all_sync(0xffffffffu, ld_acquire(f) == tag)) break;
            __nanosleep(100);
          }
          __syncwarp();
          if (lane == 0) mbar_arrive(bar_pass + p * 8);
        }
      }
    }
  } else {
    asm volatile("setmaxnreg.inc.sync.aligned.u32 232;");
    const int wg = warp >> 2, w = warp & 3;
    const int g = lane >> 2, t = lane & 3;
    const int tw = tid & 127;
    const uint32_t stage = sbase + SM_STAGE + wg * 16384;
    const uint32_t dlo = ((sbase & 0x3FFFFu) >> 4) | ((8192u >> 4) << 16);
    const int slab1 = (2 * ti1 + wg) * 4 + w;
    const int slabA = (2 * tiA + wg) * 4 + w, rowA = slabA * 16 + g;
    const int slabB = rtB * 4 + w, rowB = slabB * 16 + g, tjB = 2 * jjB + wg;
    auto wait_stage = [&](int n) { mbar_wait(bar_full + (n % NST) * 8, (n / NST) & 1); };
    auto wg_wait1 = [&]() { wgmma_wait<1>(); };
    auto rel_stage = [&](int n, int weight) {
      if (tw < 2) mbar_arrive_cluster(bar_empty + (n % NST) * 8, tw, weight);
    };
    auto desc_at = [&](int n, int off) { return make_desc(dlo + (n % NST) * (STAGE_BYTES >> 4) + (off >> 4)); };
    auto order_wait = [&]() { asm volatile("bar.sync %0, 256;" ::"r"(7 + wg) : "memory"); };
    auto order_arrive = [&]() { asm volatile("bar.arrive %0, 256;" ::"r"(8 - wg) : "memory"); };
    if (wg == 1) order_arrive();
    auto publish = [&](int ev) { __syncwarp(); if (lane == 0) mbar_arrive(bar_pub + (2 * ev + wg) * 8); };

    uint32_t a[32][4];
    float r0, r1;
    {
      uint4 rp[6];
      {
        const __nv_bfloat16* src = ((b >> 6) ? prm.w_up : prm.w_gate) + (size_t)(64 * ((b >> 3) & 7)) * FF + 176 * (b & 7);
        const int nch = ((b & 7) == 7) ? 18 : 22;
#pragma unroll
        for (int u = 0; u < 6; ++u) {
          const int idx = u * 256 + tid;
          const int r = idx / 22, cc = idx - r * 22;
          rp[u] = make_uint4(0, 0, 0, 0);
          if (idx < 1408 && cc < nch) rp[u] = ldg_nc(reinterpret_cast<const uint4*>(src + (size_t)r * FF + cc * 8));
        }
      }
      asm volatile("barrier.cluster.wait.aligned;" ::: "memory");
      float s[2][4] = {}, q1[2][4] = {}, q2[2][4] = {};
      float f0 = 0.f, f1 = 0.f, f2 = 0.f, f3 = 0.f;
      constexpr uint32_t ONES = 0x3F803F80u;
#pragma unroll
      for (int c = 0; c < 4; ++c) {
        const int n = N_X + 2 * c + wg;
        wait_stage(n);
        const int xrow = w * 16 + ((lane >> 3) & 1) * 8 + (lane & 7);
        const uint32_t xs = sbase + (n % NST) * STAGE_BYTES + xrow * 128;
#pragma unroll
        for (int kk = 0; kk < 8; ++kk) {
          const int k = 8 * c + kk;
          ldmatrix_x4(xs + (kk >> 2) * 8192 + (((2 * (kk & 3) + (lane >> 4)) ^ (xrow & 7)) << 4), a[k][0], a[k][1], a[k][2], a[k][3]);
          mma16816(s[kk & 1], a[k][0], a[k][1], a[k][2], a[k][3], ONES, ONES);
          if (kk & 1) {
            f0 = fmaf(bf_lo(a[k][0]), bf_lo(a[k][0]), f0); f0 = fmaf(bf_hi(a[k][0]), bf_hi(a[k][0]), f0);
            f1 = fmaf(bf_lo(a[k][1]), bf_lo(a[k][1]), f1); f1 = fmaf(bf_hi(a[k][1]), bf_hi(a[k][1]), f1);
            f2 = fmaf(bf_lo(a[k][2]), bf_lo(a[k][2]), f2); f2 = fmaf(bf_hi(a[k][2]), bf_hi(a[k][2]), f2);
            f3 = fmaf(bf_lo(a[k][3]), bf_lo(a[k][3]), f3); f3 = fmaf(bf_hi(a[k][3]), bf_hi(a[k][3]), f3);
          } else {
            mma16816(q1[(kk >> 1) & 1], a[k][0], a[k][1], a[k][2], a[k][3], a[k][0], a[k][2]);
            mma16816(q2[(kk >> 1) & 1], a[k][0], a[k][1], a[k][2], a[k][3], a[k][1], a[k][3]);
          }
        }
        named_bar(1 + wg);
        rel_stage(n, 2);
      }
      const int srcl = g * 4 + (g >> 1);
      f0 += f2; f1 += f3;
      f0 += __shfl_xor_sync(0xffffffffu, f0, 1); f1 += __shfl_xor_sync(0xffffffffu, f1, 1);
      f0 += __shfl_xor_sync(0xffffffffu, f0, 2); f1 += __shfl_xor_sync(0xffffffffu, f1, 2);
      const float ssq0 = f0 + __shfl_sync(0xffffffffu, (g & 1) ? q1[0][1] + q1[1][1] : q1[0][0] + q1[1][0], srcl);
      const float ssq1 = f1 + __shfl_sync(0xffffffffu, (g & 1) ? q2[0][3] + q2[1][3] : q2[0][2] + q2[1][2], srcl);
      const float mean0 = (s[0][0] + s[1][0]) * (1.0f / DM), mean1 = (s[0][2] + s[1][2]) * (1.0f / DM);
      const float var0 = fmaxf(ssq0 * (1.0f / DM) - mean0 * mean0, 0.f);
      const float var1 = fmaxf(ssq1 * (1.0f / DM) - mean1 * mean1, 0.f);
      uint32_t m0, m1;
      ln_params(mean0, var0, m0, r0);
      ln_params(mean1, var1, m1, r1);
#pragma unroll
      for (int k = 0; k < 32; ++k) {
        a[k][0] = hsub2_bf16(a[k][0], m0);
        a[k][1] = hsub2_bf16(a[k][1], m1);
        a[k][2] = hsub2_bf16(a[k][2], m0);
        a[k][3] = hsub2_bf16(a[k][3], m1);
      }
      {
        uint4* dst = g_wgu + (size_t)(((b & 7) * 24 + ((b >> 3) & 7)) * 2 + (b >> 6)) * 512;
        const int nch = ((b & 7) == 7) ? 18 : 22;
#pragma unroll
        for (int u = 0; u < 6; ++u) {
          const int idx = u * 256 + tid;
          const int r = idx / 22, cc = idx - r * 22;
          if (idx < 1408 && cc < nch) dst[(cc >> 3) * 8 * 1024 + r * 8 + ((cc & 7) ^ (r & 7))] = rp[u];
        }
      }
    }
    mbar_wait(bar_epoch, 0);
    const uint32_t epoch = *reinterpret_cast<volatile uint32_t*>(smem + SM_MISC);
    const uint32_t tag = epoch + 1;
    const int par = epoch & 1;
    const uint4* hhsrc = g_hh + slabB * 88 * 32 + lane;
    auto load_group = [&](int slot, int n) {
      const int p = n >> 2;
      const uint4* s = hhsrc + (11 * (((2 * n) & 7) + wg) + 4 * p) * 32;
#pragma unroll
      for (int ks = 0; ks < 4; ++ks) {
        if (ks < 3 || p < 2) {
          const uint4 v = ldg_cg(s + ks * 32);
          a[4 * slot + ks][0] = v.x; a[4 * slot + ks][1] = v.y; a[4 * slot + ks][2] = v.z; a[4 * slot + ks][3] = v.w;
        }
      }
    };
    auto wait_pass = [&](int p) { mbar_wait(bar_pass + p * 8, 0); };
    auto gemm_k512 = [&](float (&acc)[64], int n0, auto narrow, auto prep) {
      asm volatile("" : "+r"(n0));
      int st = n0 % NST, ph = (n0 / NST) & 1, prev = 0;
#pragma unroll
      for (int kt = 0; kt < 8; ++kt) {
        prep(kt);
        if ((kt & 3) == 0) order_wait();
        { mbar_wait(bar_full + st * 8, ph); }
        wgmma_fence();
        const uint32_t d0 = dlo + st * (STAGE_BYTES >> 4);
#pragma unroll
        for (int ks = 0; ks < 4; ++ks) {
          const int k = 4 * kt + ks;
          if constexpr (decltype(narrow)::value)
            wgmma_rs_n112(*reinterpret_cast<float (*)[56]>(&acc[0]), a[k][0], a[k][1], a[k][2], a[k][3], make_desc(d0 + ks * 128), k > 0);
          else
            wgmma_rs_n128(acc, a[k][0], a[k][1], a[k][2], a[k][3], make_desc(d0 + ks * 128), k > 0);
        }
        wgmma_commit();
        if ((kt & 3) == 3 && !(decltype(narrow)::value && kt == 7 && wg == 1)) order_arrive();
        if (kt > 0) {
          wg_wait1();
          if (tw < 2) mbar_arrive_cluster(bar_empty + prev * 8, tw, 1);
          if constexpr (decltype(narrow)::value) {
            if (kt == 1) wait_pass(0);
            if (kt <= 4) load_group(kt - 1, kt - 1);
          }
        }
        prev = st;
        if (++st == NST) { st = 0; ph ^= 1; }
      }
      wgmma_wait<0>();
      if (tw < 2) mbar_arrive_cluster(bar_empty + prev * 8, tw, 1);

    };
    {
      float acc[64];
      gemm_k512(acc, N_KV, std::false_type{}, [](int) {});
      {
        const int mrow = w * 16 + ((lane >> 3) & 1) * 8 + (lane & 7);
        const int mch = lane >> 4;
#pragma unroll
        for (int hh = 0; hh < 4; ++hh) {
          const uint32_t off = mrow * 128 + (((2 * hh + mch) ^ (mrow & 7)) << 4);
          stmatrix_x4(stage + off, phi_pack(acc[8 * hh + 0] * r0, acc[8 * hh + 1] * r0), phi_pack(acc[8 * hh + 2] * r1, acc[8 * hh + 3] * r1),
                      phi_pack(acc[8 * hh + 4] * r0, acc[8 * hh + 5] * r0), phi_pack(acc[8 * hh + 6] * r1, acc[8 * hh + 7] * r1));
          stmatrix_x4(stage + 8192 + off, pack_bf16(acc[32 + 8 * hh + 0] * r0, acc[32 + 8 * hh + 1] * r0),
                      pack_bf16(acc[32 + 8 * hh + 2] * r1, acc[32 + 8 * hh + 3] * r1),
                      pack_bf16(acc[32 + 8 * hh + 4] * r0, acc[32 + 8 * hh + 5] * r0),
                      pack_bf16(acc[32 + 8 * hh + 6] * r1, acc[32 + 8 * hh + 7] * r1));
        }
      }
      named_bar(1 + wg);
    }
    {
      constexpr uint32_t ONES = 0x3F803F80u;
      float d0[4] = {}, d1[4] = {}, z0[4] = {}, z1[4] = {};
#pragma unroll
      for (int ks = 0; ks < 4; ++ks) {
        uint32_t va0, va1, va2, va3, pb0, pb1, pb2, pb3;
        {
          const int r = 16 * ks + (lane >> 4) * 8 + (lane & 7);
          const int ch = 2 * w + ((lane >> 3) & 1);
          ldmatrix_x4_trans(stage + 8192 + r * 128 + ((ch ^ (r & 7)) << 4), va0, va1, va2, va3);
        }
        {
          const int r = 16 * ks + ((lane >> 3) & 1) * 8 + (lane & 7);
          const int ch = 2 * w + (lane >> 4);
          ldmatrix_x4_trans(stage + r * 128 + ((ch ^ (r & 7)) << 4), pb0, pb1, pb2, pb3);
        }
        mma16816(d0, va0, va1, va2, va3, pb0, pb1);
        mma16816(d1, va0, va1, va2, va3, pb2, pb3);
        mma16816(z0, ONES, ONES, ONES, ONES, pb0, pb1);
        mma16816(z1, ONES, ONES, ONES, ONES, pb2, pb3);
      }
      const int head = 4 * tj1 + w;
      float4* kvp = &g_kv[par][(head * 32 + lane) * 2];
      red_add_v4(kvp, d0[0], d0[1], d1[0], d1[1]);
      red_add_v4(kvp + 1, d0[2], d0[3], d1[2], d1[3]);
      if (g == 0) red_add_v4(&g_z[par][head * 4 + t], z0[0], z0[1], z1[0], z1[1]);
      asm volatile("fence.proxy.async.global;" ::: "memory");
      publish(0);
    }
    {
      {
        float accq[32];
        order_wait();
#pragma unroll
        for (int kt = 0; kt < 8; ++kt) {
          if ((kt & 1) == 0) wait_stage(N_Q + (kt >> 1));
          wgmma_fence();
#pragma unroll
          for (int ks = 0; ks < 4; ++ks) {
            const int k = 4 * kt + ks;
            wgmma_rs_n64(accq, a[k][0], a[k][1], a[k][2], a[k][3], desc_at(N_Q + (kt >> 1), (kt & 1) * 8192 + ks * 2048), k > 0);
          }
          wgmma_commit();
          if (kt == 7) order_arrive();
          if (kt > 0) {
            wg_wait1();
            if ((kt & 1) == 0) rel_stage(N_Q + (kt >> 1) - 1, 1);
          }
        }
        wgmma_wait<0>();
        rel_stage(N_Q + 3, 1);
#pragma unroll
        for (int hh = 0; hh < 4; ++hh)
          st_x(&g_pq[par][(slab1 * 32 + 4 * tj1 + hh) * 32 + lane], phi_pack(accq[8 * hh + 0] * r0, accq[8 * hh + 1] * r0),
               phi_pack(accq[8 * hh + 2] * r1, accq[8 * hh + 3] * r1), phi_pack(accq[8 * hh + 4] * r0, accq[8 * hh + 5] * r0),
               phi_pack(accq[8 * hh + 6] * r1, accq[8 * hh + 7] * r1));
      }
      if (b < 32) {
        g_kv[par ^ 1][b * 64 + (tid & 63)] = make_float4(0.f, 0.f, 0.f, 0.f);
        if (tid < 4) g_z[par ^ 1][b * 4 + tid] = make_float4(0.f, 0.f, 0.f, 0.f);
      }
    }

    auto cross_reduce = [&](float (&acc)[64], float (&out)[32]) {
      float4* mine = reinterpret_cast<float4*>(smem + SM_STAGE + wg * 16384) + tw;
      const float4* theirs = reinterpret_cast<const float4*>(smem + SM_STAGE + (wg ^ 1) * 16384) + tw;
#pragma unroll
      for (int i = 0; i < 8; ++i)
        mine[i * 128] = wg ? make_float4(acc[4 * i], acc[4 * i + 1], acc[4 * i + 2], acc[4 * i + 3])
                           : make_float4(acc[32 + 4 * i], acc[32 + 4 * i + 1], acc[32 + 4 * i + 2], acc[32 + 4 * i + 3]);
      asm volatile("bar.sync 4, 256;" ::: "memory");
#pragma unroll
      for (int i = 0; i < 8; ++i) {
        const float4 v = theirs[i * 128];
        out[4 * i + 0] = (wg ? acc[32 + 4 * i + 0] : acc[4 * i + 0]) + v.x;
        out[4 * i + 1] = (wg ? acc[32 + 4 * i + 1] : acc[4 * i + 1]) + v.y;
        out[4 * i + 2] = (wg ? acc[32 + 4 * i + 2] : acc[4 * i + 2]) + v.z;
        out[4 * i + 3] = (wg ? acc[32 + 4 * i + 3] : acc[4 * i + 3]) + v.w;
      }
    };

    {
      uint32_t xr[4][4];
#pragma unroll
      for (int q = 0; q < 4; ++q) {
        const uint32_t* p0 = reinterpret_cast<const uint32_t*>(prm.x + (size_t)rowB * DM + 64 * tjB + 16 * q + 2 * t);
        xr[q][0] = __ldg(p0);
        xr[q][1] = __ldg(p0 + 8 * DM / 2);
        xr[q][2] = __ldg(p0 + 4);
        xr[q][3] = __ldg(p0 + 8 * DM / 2 + 4);
      }
      const uint4* osrc = &g_pq[par][(slabB * 32 + 16 * wg) * 32];
      uint4 of[16];
      poll_sources<0u>(osrc, 4, 3, lane);
      fetch<16>(of, osrc + lane);
      mbar_wait(bar_kv, 0);
      if (b == 0 && tid == 0) asm volatile("st.relaxed.gpu.global.u32 [%0], %1;" ::"l"(&g_epoch), "r"(tag) : "memory");
      {
#pragma unroll
        for (int it = 0; it < 4; ++it) {
          const int e = (16 * wg) * 32 + tw + 128 * it;
          const float4 lo = ldg_cg_f4(&g_kv[par][e * 2]), hi = ldg_cg_f4(&g_kv[par][e * 2 + 1]);
          *reinterpret_cast<uint4*>(smem + SM_STAGE + wg * 16384 + (tw + 128 * it) * 16) =
              make_uint4(pack_bf16(lo.x, lo.y), pack_bf16(lo.z, lo.w), pack_bf16(hi.x, hi.y), pack_bf16(hi.z, hi.w));
        }
        if (tw < 64) {
          const float4 zz = ldg_cg_f4(&g_z[par][64 * wg + tw]);
          *reinterpret_cast<uint2*>(smem + SM_STAGE + wg * 16384 + 8192 + tw * 8) = make_uint2(pack_bf16(zz.x, zz.y), pack_bf16(zz.z, zz.w));
        }
      }
      named_bar(1 + wg);
      float acc[64];
#pragma unroll
      for (int n = 0; n < 4; ++n) {
        const int sn = N_WO + 2 * n + wg;
        { ensure<4, 0u>(&of[4 * n], osrc + lane + 4 * n * 32); }
#pragma unroll
        for (int ks = 0; ks < 4; ++ks) {
          const int hl = 4 * n + ks;
          const uint4 kf = *reinterpret_cast<const uint4*>(smem + SM_STAGE + wg * 16384 + (hl * 32 + lane) * 16);
          const uint2 zf = *reinterpret_cast<const uint2*>(smem + SM_STAGE + wg * 16384 + 8192 + (hl * 4 + t) * 8);
          uint4& p = of[hl];
          float n0[4] = {}, n1[4] = {}, dn[4] = {};
          mma16816(dn, p.x, p.y, p.z, p.w, zf.x, zf.y);
          mma16816(n0, p.x, p.y, p.z, p.w, kf.x, kf.y);
          mma16816(n1, p.x, p.y, p.z, p.w, kf.z, kf.w);
          const float i0 = rcp_approx(dn[0] + 1e-6f), i1 = rcp_approx(dn[2] + 1e-6f);
          p = make_uint4(pack_bf16(n0[0] * i0, n0[1] * i0), pack_bf16(n0[2] * i1, n0[3] * i1), pack_bf16(n1[0] * i0, n1[1] * i0),
                         pack_bf16(n1[2] * i1, n1[3] * i1));
        }
        wait_stage(sn);
        wgmma_fence();
#pragma unroll
        for (int ks = 0; ks < 4; ++ks)
          wgmma_rs_n128(acc, of[4 * n + ks].x, of[4 * n + ks].y, of[4 * n + ks].z, of[4 * n + ks].w, desc_at(sn, ks * 2048), (n | ks) > 0);
        wgmma_commit();
        if (n > 0) {
          wg_wait1();
          rel_stage(sn - 2, 2);
        }
      }
      wgmma_wait<0>();
      rel_stage(N_WO + 6 + wg, 2);
      named_bar(1 + wg);
      float sum[32];
      cross_reduce(acc, sum);

      uint32_t hf[4][4];
      float s0 = 0.f, s1 = 0.f;
#pragma unroll
      for (int q = 0; q < 4; ++q) {
#pragma unroll
        for (int r = 0; r < 4; ++r) {
          hf[q][r] = hadd2_bf16(xr[q][r], pack_bf16(sum[8 * q + 2 * r], sum[8 * q + 2 * r + 1]));
          const float sv = bf_lo(hf[q][r]) + bf_hi(hf[q][r]);
          if (r & 1) s1 += sv; else s0 += sv;
        }
        st_x(g_h + (slabB * 32 + 4 * tjB + q) * 32 + lane, hf[q][0], hf[q][1], hf[q][2], hf[q][3]);
      }
      s0 += __shfl_xor_sync(0xffffffffu, s0, 1); s1 += __shfl_xor_sync(0xffffffffu, s1, 1);
      s0 += __shfl_xor_sync(0xffffffffu, s0, 2); s1 += __shfl_xor_sync(0xffffffffu, s1, 2);
      const float mu0 = s0 * (1.0f / 64), mu1 = s1 * (1.0f / 64);
      float e0 = 0.f, e1 = 0.f;
#pragma unroll
      for (int q = 0; q < 4; ++q) {
#pragma unroll
        for (int r = 0; r < 4; ++r) {
          const float mu = (r & 1) ? mu1 : mu0;
          const float dl = bf_lo(hf[q][r]) - mu, dh = bf_hi(hf[q][r]) - mu;
          const float sv = dl * dl + dh * dh;
          if (r & 1) e1 += sv; else e0 += sv;
        }
      }
      e0 += __shfl_xor_sync(0xffffffffu, e0, 1); e1 += __shfl_xor_sync(0xffffffffu, e1, 1);
      e0 += __shfl_xor_sync(0xffffffffu, e0, 2); e1 += __shfl_xor_sync(0xffffffffu, e1, 2);
      if (t < 2) {
        const uint64_t pk = t == 0 ? ((uint64_t)__float_as_uint(e0) << 32 | __float_as_uint(mu0)) : ((uint64_t)__float_as_uint(e1) << 32 | __float_as_uint(mu1));
        const uint64_t* dst = reinterpret_cast<const uint64_t*>(g_hstat) + (rowB + 8 * t) * 8 + tjB;
        asm volatile("st.relaxed.gpu.global.u64 [%0], %1;" ::"l"(dst), "l"(pk) : "memory");
      }
    }

    {
      const uint4* hsrc = g_h + slabA * 32 * 32;
      uint32_t m0, m1;
      {
#pragma unroll 1
        for (int it = 0; it < SPIN_LIMIT; ++it) {
          const uint4 q = ld_x(&g_hstat[slabA * 64 + t]);
          if (!__any_sync(0xffffffffu, q.x == POISON || q.z == POISON)) break;
        }
        uint4 p0 = ld_x(&g_hstat[rowA * 4 + t]), p1 = ld_x(&g_hstat[(rowA + 8) * 4 + t]);
#pragma unroll
        for (int k = 0; k < 32; ++k) {
          const uint4 v = ld_x(hsrc + lane + k * 32);
          a[k][0] = v.x; a[k][1] = v.y; a[k][2] = v.z; a[k][3] = v.w;
        }
#pragma unroll 1
        for (int it = 0; it < SPIN_LIMIT; ++it) {
          if (!__any_sync(0xffffffffu, p0.x == POISON || p0.z == POISON || p1.x == POISON || p1.z == POISON)) break;
          p0 = ld_x(&g_hstat[rowA * 4 + t]);
          p1 = ld_x(&g_hstat[(rowA + 8) * 4 + t]);
        }
        const float a0x = __uint_as_float(p0.x), a0y = __uint_as_float(p0.y), a0z = __uint_as_float(p0.z), a0w = __uint_as_float(p0.w);
        const float a1x = __uint_as_float(p1.x), a1y = __uint_as_float(p1.y), a1z = __uint_as_float(p1.z), a1w = __uint_as_float(p1.w);
        float a0 = a0x + a0z, a1 = a1x + a1z;
        a0 += __shfl_xor_sync(0xffffffffu, a0, 1); a1 += __shfl_xor_sync(0xffffffffu, a1, 1);
        a0 += __shfl_xor_sync(0xffffffffu, a0, 2); a1 += __shfl_xor_sync(0xffffffffu, a1, 2);
        const float mean0 = a0 * 0.125f, mean1 = a1 * 0.125f;
        float v0 = a0y + a0w + 64.f * ((a0x - mean0) * (a0x - mean0) + (a0z - mean0) * (a0z - mean0));
        float v1 = a1y + a1w + 64.f * ((a1x - mean1) * (a1x - mean1) + (a1z - mean1) * (a1z - mean1));
        v0 += __shfl_xor_sync(0xffffffffu, v0, 1); v1 += __shfl_xor_sync(0xffffffffu, v1, 1);
        v0 += __shfl_xor_sync(0xffffffffu, v0, 2); v1 += __shfl_xor_sync(0xffffffffu, v1, 2);
        ln_params(mean0, v0 * (1.0f / DM), m0, r0);
        ln_params(mean1, v1 * (1.0f / DM), m1, r1);
      }
      auto prep_h = [&](int kt) {
        if (__builtin_expect(__any_sync(0xffffffffu, a[4 * kt][0] == POISON || a[4 * kt + 1][0] == POISON || a[4 * kt + 2][0] == POISON || a[4 * kt + 3][0] == POISON), 0)) {
#pragma unroll 1
          for (int it = 0; it < SPIN_LIMIT; ++it) {
            uint4 v[4];
            fetch<4>(v, hsrc + lane + 4 * kt * 32);
#pragma unroll
            for (int ks = 0; ks < 4; ++ks) { a[4 * kt + ks][0] = v[ks].x; a[4 * kt + ks][1] = v[ks].y; a[4 * kt + ks][2] = v[ks].z; a[4 * kt + ks][3] = v[ks].w; }
            if (!any_poison<4>(v)) break;
          }
        }

#pragma unroll
        for (int ks = 0; ks < 4; ++ks) {
          a[4 * kt + ks][0] = hsub2_bf16(a[4 * kt + ks][0], m0);
          a[4 * kt + ks][1] = hsub2_bf16(a[4 * kt + ks][1], m1);
          a[4 * kt + ks][2] = hsub2_bf16(a[4 * kt + ks][2], m0);
          a[4 * kt + ks][3] = hsub2_bf16(a[4 * kt + ks][3], m1);
        }
      };
#pragma unroll 1
      for (int p = 0; p < 3; ++p) {
        float acc[64];
        if (p == 0) gemm_k512(acc, N_GU + 8 * p, std::false_type{}, prep_h);
        else if (p == 1) gemm_k512(acc, N_GU + 8 * p, std::false_type{}, [](int) {});
        else gemm_k512(acc, N_GU + 8 * p, std::true_type{}, [](int) {});
#pragma unroll
        for (int qq = 0; qq < 4; ++qq) {
          if (qq < 3 || p < 2) {
            uint32_t v[4];
#pragma unroll
            for (int r = 0; r < 4; ++r) {
              const float sc = (r & 1) ? r1 : r0;
              v[r] = hmul2_bf16(pack_bf16(acc[8 * qq + 2 * r] * sc, acc[8 * qq + 2 * r + 1] * sc),
                                pack_bf16(acc[32 + 8 * qq + 2 * r] * sc, acc[32 + 8 * qq + 2 * r + 1] * sc));
            }
            g_hh[(slabA * 88 + 11 * tjA + 4 * p + qq) * 32 + lane] = make_uint4(v[0], v[1], v[2], v[3]);
          }
        }
        publish(1 + p);
      }
    }

    {
      float acc[64];
#pragma unroll
      for (int n = 0; n < 12; ++n) {
        const int sn = N_DN + 2 * n + wg;
        const int sl = n & 7;
        if (n == 4) { wait_pass(2); }
        wait_stage(sn);
        wgmma_fence();
#pragma unroll
        for (int ks = 0; ks < 4; ++ks)
          if (ks < 3 || n < 8)
            wgmma_rs_n128(acc, a[4 * sl + ks][0], a[4 * sl + ks][1], a[4 * sl + ks][2], a[4 * sl + ks][3], desc_at(sn, ks * 2048), (n | ks) > 0);
        wgmma_commit();
        if (n == 0) {
          wait_pass(1);
#pragma unroll
          for (int m = 4; m < 8; ++m) load_group(m, m);
        }
        if (n > 0) {
          wg_wait1();
          if (sn - 2 + NST < NSTAGES) rel_stage(sn - 2, 2);
          if (n >= 4 && n < 8) load_group(n - 4, n + 4);
        }
      }
      uint4 hf[4];
#pragma unroll
      for (int q = 0; q < 4; ++q) hf[q] = g_h[(slabB * 32 + 4 * tjB + q) * 32 + lane];
      wgmma_wait<0>();
      float sum[32];
      cross_reduce(acc, sum);
      const uint32_t wst = sbase + warp * 2048;
      {
        const int mrow = ((lane >> 3) & 1) * 8 + (lane & 7);
        const int mch = lane >> 4;
#pragma unroll
        for (int q = 0; q < 4; ++q) {
          stmatrix_x4(wst + mrow * 128 + (((2 * q + mch) ^ (mrow & 7)) << 4),
                      hadd2_bf16(hf[q].x, pack_bf16(sum[8 * q + 0], sum[8 * q + 1])), hadd2_bf16(hf[q].y, pack_bf16(sum[8 * q + 2], sum[8 * q + 3])),
                      hadd2_bf16(hf[q].z, pack_bf16(sum[8 * q + 4], sum[8 * q + 5])), hadd2_bf16(hf[q].w, pack_bf16(sum[8 * q + 6], sum[8 * q + 7])));
        }
      }
      __syncwarp();
#pragma unroll
      for (int it = 0; it < 4; ++it) {
        const int r = it * 4 + (lane >> 3), ch = lane & 7;
        uint4 v;
        asm volatile("ld.shared.v4.u32 {%0,%1,%2,%3}, [%4];" : "=r"(v.x), "=r"(v.y), "=r"(v.z), "=r"(v.w) : "r"(wst + r * 128 + ((ch ^ (r & 7)) << 4)));
        *reinterpret_cast<uint4*>(prm.out + (size_t)(slabB * 16 + r) * DM + 64 * tjB + ch * 8) = v;
      }
    }
  }
  asm volatile("barrier.cluster.arrive.relaxed.aligned;\nbarrier.cluster.wait.aligned;" ::: "memory");
}

typedef CUresult (*EncodeTiledFn)(CUtensorMap*, CUtensorMapDataType, cuuint32_t, void*, const cuuint64_t*, const cuuint64_t*,
                                  const cuuint32_t*, const cuuint32_t*, CUtensorMapInterleave, CUtensorMapSwizzle,
                                  CUtensorMapL2promotion, CUtensorMapFloatOOBfill);

void encode_blk(EncodeTiledFn enc, CUtensorMap* tm, const void* p, int rows, int cols, int box_rows, int box_blks) {
  cuuint64_t gd[3] = {64, (cuuint64_t)rows, (cuuint64_t)cols / 64};
  cuuint64_t gs[2] = {(cuuint64_t)cols * 2, 128};
  cuuint32_t bx[3] = {64, (cuuint32_t)box_rows, (cuuint32_t)box_blks};
  cuuint32_t es[3] = {1, 1, 1};
  enc(tm, CU_TENSOR_MAP_DATA_TYPE_BFLOAT16, 3, const_cast<void*>(p), gd, gs, bx, es, CU_TENSOR_MAP_INTERLEAVE_NONE,
      CU_TENSOR_MAP_SWIZZLE_128B, CU_TENSOR_MAP_L2_PROMOTION_L2_128B, CU_TENSOR_MAP_FLOAT_OOB_FILL_NONE);
}

}

extern "C" void kernel_launch(void* const* d_in, const int* in_sizes, int n_in, void* d_out, int out_size) {
  (void)in_sizes; (void)n_in; (void)out_size;
  static CUtensorMap tm_x, tm_qkv, tm_wo, tm_down64, tm_down48;
  static const void* cached[4] = {nullptr, nullptr, nullptr, nullptr};
  static bool attr_done = false;
  const void* ptrs[4] = {d_in[1], d_in[2], d_in[6], d_in[0]};
  bool same = true;
  for (int i = 0; i < 4; ++i) same = same && (cached[i] == ptrs[i]);
  if (!same) {
    void* fn = nullptr;
    cudaDriverEntryPointQueryResult qr;
    cudaGetDriverEntryPoint("cuTensorMapEncodeTiled", &fn, cudaEnableDefault, &qr);
    EncodeTiledFn enc = (EncodeTiledFn)fn;
    encode_blk(enc, &tm_qkv, ptrs[0], DM, 3 * DM, 64, 1);
    encode_blk(enc, &tm_wo, ptrs[1], DM, DM, 64, 2);
    encode_blk(enc, &tm_down64, ptrs[2], FF, DM, 64, 2);
    encode_blk(enc, &tm_down48, ptrs[2], FF, DM, 48, 1);
    encode_blk(enc, &tm_x, ptrs[3], 2048, DM, 64, 2);
    for (int i = 0; i < 4; ++i) cached[i] = ptrs[i];
  }
  if (!attr_done) {
    cudaFuncSetAttribute(fused_block_kernel, cudaFuncAttributeMaxDynamicSharedMemorySize, SM_TOTAL);
    attr_done = true;
  }
  Params prm;
  prm.x = (const __nv_bfloat16*)d_in[0];
  prm.w_gate = (const __nv_bfloat16*)d_in[4];
  prm.w_up = (const __nv_bfloat16*)d_in[5];
  prm.out = (__nv_bfloat16*)d_out;
  cudaLaunchConfig_t cfg = {};
  cfg.gridDim = dim3(NCTA);
  cfg.blockDim = dim3(384);
  cfg.dynamicSmemBytes = SM_TOTAL;
  cfg.stream = cudaStreamPerThread;
  cudaLaunchAttribute at[1];
  at[0].id = cudaLaunchAttributeClusterDimension;
  at[0].val.clusterDim.x = 2;
  at[0].val.clusterDim.y = 1;
  at[0].val.clusterDim.z = 1;
  cfg.attrs = at;
  cfg.numAttrs = 1;
  cudaLaunchKernelEx(&cfg, fused_block_kernel, tm_x, tm_qkv, tm_wo, tm_down64, tm_down48, prm);
}
```

```cpp
#include <cuda_runtime.h>
#include <cuda_bf16.h>
#include <cuda.h>
#include <stdint.h>
#include <type_traits>

namespace {

constexpr int DM = 512;
constexpr int FF = 1376;
constexpr int NCTA = 128;
constexpr int NST = 12;
constexpr int STAGE_BYTES = 16384;
constexpr int N_X = 0, N_KV = 8, N_Q = 16, N_WO = 20, N_GU = 28, N_DN = 52, NSTAGES = 64;

constexpr int SM_STAGE = NST * STAGE_BYTES;
constexpr int SM_BAR = SM_STAGE + 32768;
constexpr int SM_EBAR = SM_BAR + 2 * NST * 8;
constexpr int SM_KBAR = SM_EBAR + 8;
constexpr int SM_PBAR = SM_KBAR + 8;
constexpr int SM_UBAR = SM_PBAR + 48;
constexpr int SM_MISC = SM_UBAR + 64;
constexpr int SM_TOTAL = SM_MISC + 16;

constexpr int SPIN_LIMIT = 1 << 18;
constexpr uint32_t POISON = 0xFFFFFFFFu;

__device__ uint4 g_pq[2][128 * 32 * 32];
__device__ uint4 g_h[128 * 32 * 32];
__device__ uint4 g_hh[128 * 88 * 32];
__device__ uint4 g_hstat[2048 * 4];
__device__ float4 g_kv[2][32 * 32 * 2];
__device__ float4 g_z[2][32 * 4];
__device__ uint4 g_wgu[8 * 3 * 8 * 2 * 512];
__device__ uint32_t g_hhflag[32 * 3 * 8];
__device__ uint32_t g_kvcnt[8 * 32];
__device__ uint32_t g_epoch;

__device__ __forceinline__ uint32_t smem_u32(const void* p) { return (uint32_t)__cvta_generic_to_shared(p); }
__device__ __forceinline__ void mbar_init(uint32_t bar, uint32_t cnt) {
  asm volatile("mbarrier.init.shared::cta.b64 [%0], %1;" ::"r"(bar), "r"(cnt) : "memory");
}
__device__ __forceinline__ void mbar_expect_tx(uint32_t bar, uint32_t bytes) {
  asm volatile("mbarrier.arrive.expect_tx.shared::cta.b64 _, [%0], %1;" ::"r"(bar), "r"(bytes) : "memory");
}
__device__ __forceinline__ void mbar_arrive(uint32_t bar) {
  asm volatile("mbarrier.arrive.shared::cta.b64 _, [%0];" ::"r"(bar) : "memory");
}
__device__ __forceinline__ void mbar_wait(uint32_t bar, uint32_t parity) {
  asm volatile(
      "{\n.reg .pred p;\n.reg .u32 c;\nmov.u32 c, 0;\n"
      "W%=:\nmbarrier.try_wait.parity.shared::cta.b64 p, [%0], %1;\n@p bra D%=;\n"
      "add.u32 c, c, 1;\nsetp.lt.u32 p, c, %2;\n@p bra W%=;\nD%=:\n}\n" ::"r"(bar), "r"(parity), "n"(SPIN_LIMIT)
      : "memory");
}
__device__ __forceinline__ void tma_3d_mc(uint32_t dst, const CUtensorMap* tm, uint32_t bar, int c1, int c2) {
  asm volatile(
      "cp.async.bulk.tensor.3d.shared::cluster.global.mbarrier::complete_tx::bytes.multicast::cluster [%0], [%1, {%3, %4, %5}], [%2], %6;" ::"r"(dst),
      "l"((uint64_t)tm), "r"(bar), "r"(0), "r"(c1), "r"(c2), "h"((uint16_t)3)
      : "memory");
}
__device__ __forceinline__ void tma_3d(uint32_t dst, const CUtensorMap* tm, uint32_t bar, int c1, int c2) {
  asm volatile(
      "cp.async.bulk.tensor.3d.shared::cluster.global.mbarrier::complete_tx::bytes [%0], [%1, {%3, %4, %5}], [%2];" ::"r"(dst),
      "l"((uint64_t)tm), "r"(bar), "r"(0), "r"(c1), "r"(c2)
      : "memory");
}
__device__ __forceinline__ void bulk_g2s_mc(uint32_t dst, const void* src, uint32_t bytes, uint32_t bar) {
  asm volatile("cp.async.bulk.shared::cluster.global.mbarrier::complete_tx::bytes.multicast::cluster [%0], [%1], %2, [%3], %4;" ::"r"(dst),
               "l"(src), "r"(bytes), "r"(bar), "h"((uint16_t)3)
               : "memory");
}
__device__ __forceinline__ void mbar_arrive_cluster(uint32_t bar, uint32_t rank, uint32_t count) {
  asm volatile(
      "{\n.reg .b32 ra;\nmapa.shared::cluster.u32 ra, %0, %1;\nmbarrier.arrive.shared::cluster.b64 _, [ra], %2;\n}\n" ::"r"(bar), "r"(rank), "r"(count)
      : "memory");
}
__device__ __forceinline__ void wgmma_fence() { asm volatile("wgmma.fence.sync.aligned;" ::: "memory"); }
__device__ __forceinline__ void wgmma_commit() { asm volatile("wgmma.commit_group.sync.aligned;" ::: "memory"); }
template <int N>
__device__ __forceinline__ void wgmma_wait() { asm volatile("wgmma.wait_group.sync.aligned %0;" ::"n"(N) : "memory"); }

__device__ __forceinline__ uint64_t make_desc(uint32_t lo) {
  return (uint64_t)lo | ((uint64_t)((1024u >> 4) | (1u << 30)) << 32);
}

__device__ __forceinline__ void wgmma_rs_n64(float (&d)[32], uint32_t a0, uint32_t a1, uint32_t a2, uint32_t a3, uint64_t descB, int scaleD) {
  asm volatile(
    "{\n.reg .pred p;\nsetp.ne.b32 p, %37, 0;\n"
    "wgmma.mma_async.sync.aligned.m64n64k16.f32.bf16.bf16 "
    "{%0, %1, %2, %3, %4, %5, %6, %7, %8, %9, %10, %11, %12, %13, %14, %15, "
    "%16, %17, %18, %19, %20, %21, %22, %23, %24, %25, %26, %27, %28, %29, %30, %31}, "
    "{%32, %33, %34, %35}, %36, p, 1, 1, 1;\n}\n"
    : "+f"(d[0]), "+f"(d[1]), "+f"(d[2]), "+f"(d[3]), "+f"(d[4]), "+f"(d[5]), "+f"(d[6]), "+f"(d[7]),
      "+f"(d[8]), "+f"(d[9]), "+f"(d[10]), "+f"(d[11]), "+f"(d[12]), "+f"(d[13]), "+f"(d[14]), "+f"(d[15]),
      "+f"(d[16]), "+f"(d[17]), "+f"(d[18]), "+f"(d[19]), "+f"(d[20]), "+f"(d[21]), "+f"(d[22]), "+f"(d[23]),
      "+f"(d[24]), "+f"(d[25]), "+f"(d[26]), "+f"(d[27]), "+f"(d[28]), "+f"(d[29]), "+f"(d[30]), "+f"(d[31])
    : "r"(a0), "r"(a1), "r"(a2), "r"(a3), "l"(descB), "r"(scaleD));
}

__device__ __forceinline__ void wgmma_rs_n112(float (&d)[56], uint32_t a0, uint32_t a1, uint32_t a2, uint32_t a3, uint64_t descB, int scaleD) {
  asm volatile(
    "{\n.reg .pred p;\nsetp.ne.b32 p, %61, 0;\n"
    "wgmma.mma_async.sync.aligned.m64n112k16.f32.bf16.bf16 "
    "{%0, %1, %2, %3, %4, %5, %6, %7, %8, %9, %10, %11, %12, %13, %14, %15, "
    "%16, %17, %18, %19, %20, %21, %22, %23, %24, %25, %26, %27, %28, %29, %30, %31, "
    "%32, %33, %34, %35, %36, %37, %38, %39, %40, %41, %42, %43, %44, %45, %46, %47, "
    "%48, %49, %50, %51, %52, %53, %54, %55}, "
    "{%56, %57, %58, %59}, %60, p, 1, 1, 1;\n}\n"
    : "+f"(d[0]), "+f"(d[1]), "+f"(d[2]), "+f"(d[3]), "+f"(d[4]), "+f"(d[5]), "+f"(d[6]), "+f"(d[7]),
      "+f"(d[8]), "+f"(d[9]), "+f"(d[10]), "+f"(d[11]), "+f"(d[12]), "+f"(d[13]), "+f"(d[14]), "+f"(d[15]),
      "+f"(d[16]), "+f"(d[17]), "+f"(d[18]), "+f"(d[19]), "+f"(d[20]), "+f"(d[21]), "+f"(d[22]), "+f"(d[23]),
      "+f"(d[24]), "+f"(d[25]), "+f"(d[26]), "+f"(d[27]), "+f"(d[28]), "+f"(d[29]), "+f"(d[30]), "+f"(d[31]),
      "+f"(d[32]), "+f"(d[33]), "+f"(d[34]), "+f"(d[35]), "+f"(d[36]), "+f"(d[37]), "+f"(d[38]), "+f"(d[39]),
      "+f"(d[40]), "+f"(d[41]), "+f"(d[42]), "+f"(d[43]), "+f"(d[44]), "+f"(d[45]), "+f"(d[46]), "+f"(d[47]),
      "+f"(d[48]), "+f"(d[49]), "+f"(d[50]), "+f"(d[51]), "+f"(d[52]), "+f"(d[53]), "+f"(d[54]), "+f"(d[55])
    : "r"(a0), "r"(a1), "r"(a2), "r"(a3), "l"(descB), "r"(scaleD));
}

__device__ __forceinline__ void wgmma_rs_n128(float (&d)[64], uint32_t a0, uint32_t a1, uint32_t a2, uint32_t a3, uint64_t descB, int scaleD) {
  asm volatile(
    "{\n.reg .pred p;\nsetp.ne.b32 p, %69, 0;\n"
    "wgmma.mma_async.sync.aligned.m64n128k16.f32.bf16.bf16 "
    "{%0, %1, %2, %3, %4, %5, %6, %7, %8, %9, %10, %11, %12, %13, %14, %15, "
    "%16, %17, %18, %19, %20, %21, %22, %23, %24, %25, %26, %27, %28, %29, %30, %31, "
    "%32, %33, %34, %35, %36, %37, %38, %39, %40, %41, %42, %43, %44, %45, %46, %47, "
    "%48, %49, %50, %51, %52, %53, %54, %55, %56, %57, %58, %59, %60, %61, %62, %63}, "
    "{%64, %65, %66, %67}, %68, p, 1, 1, 1;\n}\n"
    : "+f"(d[0]), "+f"(d[1]), "+f"(d[2]), "+f"(d[3]), "+f"(d[4]), "+f"(d[5]), "+f"(d[6]), "+f"(d[7]),
      "+f"(d[8]), "+f"(d[9]), "+f"(d[10]), "+f"(d[11]), "+f"(d[12]), "+f"(d[13]), "+f"(d[14]), "+f"(d[15]),
      "+f"(d[16]), "+f"(d[17]), "+f"(d[18]), "+f"(d[19]), "+f"(d[20]), "+f"(d[21]), "+f"(d[22]), "+f"(d[23]),
      "+f"(d[24]), "+f"(d[25]), "+f"(d[26]), "+f"(d[27]), "+f"(d[28]), "+f"(d[29]), "+f"(d[30]), "+f"(d[31]),
      "+f"(d[32]), "+f"(d[33]), "+f"(d[34]), "+f"(d[35]), "+f"(d[36]), "+f"(d[37]), "+f"(d[38]), "+f"(d[39]),
      "+f"(d[40]), "+f"(d[41]), "+f"(d[42]), "+f"(d[43]), "+f"(d[44]), "+f"(d[45]), "+f"(d[46]), "+f"(d[47]),
      "+f"(d[48]), "+f"(d[49]), "+f"(d[50]), "+f"(d[51]), "+f"(d[52]), "+f"(d[53]), "+f"(d[54]), "+f"(d[55]),
      "+f"(d[56]), "+f"(d[57]), "+f"(d[58]), "+f"(d[59]), "+f"(d[60]), "+f"(d[61]), "+f"(d[62]), "+f"(d[63])
    : "r"(a0), "r"(a1), "r"(a2), "r"(a3), "l"(descB), "r"(scaleD));
}


__device__ __forceinline__ void mma16816(float (&c)[4], uint32_t a0, uint32_t a1, uint32_t a2, uint32_t a3, uint32_t b0, uint32_t b1) {
  asm("mma.sync.aligned.m16n8k16.row.col.f32.bf16.bf16.f32 {%0,%1,%2,%3}, {%4,%5,%6,%7}, {%8,%9}, {%0,%1,%2,%3};"
      : "+f"(c[0]), "+f"(c[1]), "+f"(c[2]), "+f"(c[3])
      : "r"(a0), "r"(a1), "r"(a2), "r"(a3), "r"(b0), "r"(b1));
}
__device__ __forceinline__ void stmatrix_x4(uint32_t addr, uint32_t r0, uint32_t r1, uint32_t r2, uint32_t r3) {
  asm volatile("stmatrix.sync.aligned.m8n8.x4.shared.b16 [%0], {%1,%2,%3,%4};" ::"r"(addr), "r"(r0), "r"(r1), "r"(r2), "r"(r3) : "memory");
}
__device__ __forceinline__ void ldmatrix_x4(uint32_t addr, uint32_t& r0, uint32_t& r1, uint32_t& r2, uint32_t& r3) {
  asm volatile("ldmatrix.sync.aligned.m8n8.x4.shared.b16 {%0,%1,%2,%3}, [%4];"
               : "=r"(r0), "=r"(r1), "=r"(r2), "=r"(r3)
               : "r"(addr)
               : "memory");
}
__device__ __forceinline__ void ldmatrix_x4_trans(uint32_t addr, uint32_t& r0, uint32_t& r1, uint32_t& r2, uint32_t& r3) {
  asm volatile("ldmatrix.sync.aligned.m8n8.x4.trans.shared.b16 {%0,%1,%2,%3}, [%4];"
               : "=r"(r0), "=r"(r1), "=r"(r2), "=r"(r3)
               : "r"(addr)
               : "memory");
}
__device__ __forceinline__ uint32_t pack_bf16(float lo, float hi) {
  uint32_t r;
  asm("cvt.rn.bf16x2.f32 %0, %1, %2;" : "=r"(r) : "f"(hi), "f"(lo));
  return r;
}
__device__ __forceinline__ float bf_lo(uint32_t v) { return __uint_as_float(v << 16); }
__device__ __forceinline__ float bf_hi(uint32_t v) { return __uint_as_float(v & 0xffff0000u); }
__device__ __forceinline__ float bf16r(float x) { return bf_lo(pack_bf16(x, 0.f)); }
__device__ __forceinline__ uint32_t hsub2_bf16(uint32_t a, uint32_t b) {
  uint32_t r;
  asm("sub.rn.bf16x2 %0, %1, %2;" : "=r"(r) : "r"(a), "r"(b));
  return r;
}
__device__ __forceinline__ uint32_t hadd2_bf16(uint32_t a, uint32_t b) {
  uint32_t r;
  asm("add.rn.bf16x2 %0, %1, %2;" : "=r"(r) : "r"(a), "r"(b));
  return r;
}
__device__ __forceinline__ uint32_t hmul2_bf16(uint32_t a, uint32_t b) {
  uint32_t r;
  asm("mul.rn.bf16x2 %0, %1, %2;" : "=r"(r) : "r"(a), "r"(b));
  return r;
}
__device__ __forceinline__ void ln_params(float mean, float var, uint32_t& m2, float& rinv) {
  m2 = pack_bf16(mean, mean);
  const float ve = bf16r(bf16r(var) + 1e-5f);
  rinv = 1.0f / bf16r(sqrtf(ve));
}
__device__ __forceinline__ float ex2_approx(float x) {
  float r;
  asm("ex2.approx.ftz.f32 %0, %1;" : "=f"(r) : "f"(x));
  return r;
}
__device__ __forceinline__ float rcp_approx(float x) {
  float r;
  asm("rcp.approx.ftz.f32 %0, %1;" : "=f"(r) : "f"(x));
  return r;
}
__device__ __forceinline__ uint32_t phi_pack(float a, float b) {
  const uint32_t t = pack_bf16(a, b);
  const uint32_t lin = hadd2_bf16(t, 0x3F803F80u);
  const uint32_t ex = pack_bf16(ex2_approx(bf_lo(t) * 1.4426950408889634f), ex2_approx(bf_hi(t) * 1.4426950408889634f));
  uint32_t mask;
  asm("set.gt.u32.bf16x2 %0, %1, %2;" : "=r"(mask) : "r"(t), "r"(0u));
  const uint32_t p = (lin & mask) | (ex & ~mask);
  return hadd2_bf16(p, 0x35863586u);
}
__device__ __forceinline__ uint4 ldg_nc(const uint4* p) {
  uint4 v;
  asm volatile("ld.global.nc.L1::no_allocate.v4.u32 {%0,%1,%2,%3}, [%4];" : "=r"(v.x), "=r"(v.y), "=r"(v.z), "=r"(v.w) : "l"(p));
  return v;
}
__device__ __forceinline__ uint4 ldg_cg(const uint4* p) {
  uint4 v;
  asm volatile("ld.global.cg.v4.u32 {%0,%1,%2,%3}, [%4];" : "=r"(v.x), "=r"(v.y), "=r"(v.z), "=r"(v.w) : "l"(p) : "memory");
  return v;
}
__device__ __forceinline__ float4 ldg_cg_f4(const float4* p) {
  float4 v;
  asm volatile("ld.global.cg.v4.f32 {%0,%1,%2,%3}, [%4];" : "=f"(v.x), "=f"(v.y), "=f"(v.z), "=f"(v.w) : "l"(p) : "memory");
  return v;
}
__device__ __forceinline__ uint4 ld_x(const uint4* p) {
  uint4 v;
  asm volatile("{\n.reg .b128 q;\nld.relaxed.gpu.global.b128 q, [%4];\nmov.b128 {%0,%1,%2,%3}, q;\n}\n"
               : "=r"(v.x), "=r"(v.y), "=r"(v.z), "=r"(v.w)
               : "l"(p)
               : "memory");
  return v;
}
__device__ __forceinline__ void st_x(uint4* p, uint32_t a, uint32_t b, uint32_t c, uint32_t d) {
  asm volatile("{\n.reg .b128 q;\nmov.b128 q, {%1,%2,%3,%4};\nst.relaxed.gpu.global.b128 [%0], q;\n}\n" ::"l"(p), "r"(a), "r"(b), "r"(c), "r"(d)
               : "memory");
}
__device__ __forceinline__ uint32_t ld_acquire(const uint32_t* p) {
  uint32_t v;
  asm volatile("ld.acquire.gpu.global.u32 %0, [%1];" : "=r"(v) : "l"(p) : "memory");
  return v;
}
__device__ __forceinline__ void red_add_v4(float4* p, float a, float b, float c, float d) {
  asm volatile("red.relaxed.gpu.global.add.v4.f32 [%0], {%1,%2,%3,%4};" ::"l"(p), "f"(a), "f"(b), "f"(c), "f"(d) : "memory");
}
__device__ __forceinline__ void named_bar(int id) { asm volatile("bar.sync %0, 128;" ::"r"(id) : "memory"); }

template <int N>
__device__ __forceinline__ void fetch(uint4* r, const uint4* p) {
#pragma unroll
  for (int i = 0; i < N; ++i) r[i] = ld_x(p + i * 32);
}
template <int N, uint32_t SENT = POISON>
__device__ __forceinline__ bool any_poison(const uint4* r) {
  bool bad = false;
#pragma unroll
  for (int i = 0; i < N; ++i) bad |= (r[i].x == SENT);
  return __any_sync(0xffffffffu, bad);
}
template <int N, uint32_t SENT = POISON>
__device__ __forceinline__ void ensure(uint4* r, const uint4* p) {
  if (__builtin_expect((any_poison<N, SENT>(r)), 0)) {
#pragma unroll 1
    for (int it = 0; it < SPIN_LIMIT; ++it) {
      fetch<N>(r, p);
      if (!any_poison<N, SENT>(r)) break;
    }
  }
}

template <uint32_t SENT>
__device__ __forceinline__ void poll_sources(const uint4* base, int frags_per_src, int nsrc_mask, int lane) {
  const uint32_t* p = reinterpret_cast<const uint32_t*>(base + (((lane & nsrc_mask) + 1) * frags_per_src - 1) * 32 + 31);
  uint32_t v0, v1;
  asm volatile("ld.relaxed.gpu.global.u32 %0, [%1];" : "=r"(v0) : "l"(p) : "memory");
#pragma unroll 1
  for (int it = 0; it < SPIN_LIMIT; ++it) {
    asm volatile("ld.relaxed.gpu.global.u32 %0, [%1];" : "=r"(v1) : "l"(p) : "memory");
    if (!__any_sync(0xffffffffu, v0 == SENT)) break;
    asm volatile("ld.relaxed.gpu.global.u32 %0, [%1];" : "=r"(v0) : "l"(p) : "memory");
    if (!__any_sync(0xffffffffu, v1 == SENT)) break;
  }
}

struct Params {
  const __nv_bfloat16* x;
  const __nv_bfloat16* w_gate;
  const __nv_bfloat16* w_up;
  __nv_bfloat16* out;
};

__global__ void __launch_bounds__(384, 1)
fused_block_kernel(const __grid_constant__ CUtensorMap tm_x, const __grid_constant__ CUtensorMap tm_qkv, const __grid_constant__ CUtensorMap tm_wo,
                   const __grid_constant__ CUtensorMap tm_down64, const __grid_constant__ CUtensorMap tm_down48, const Params prm) {
  extern __shared__ __align__(1024) uint8_t smem[];
  const uint32_t sbase = smem_u32(smem);
  const int tid = threadIdx.x;
  const int warp = tid >> 5, lane = tid & 31;
  const int b = blockIdx.x;
  const int cm = b & 1, cp = b >> 1;
  int dom, pos;
  if (cp < 4) { dom = 15; pos = cp; }
  else if (cp < 36) { dom = (cp - 4) & 7; pos = (cp - 4) >> 3; }
  else { dom = 8 + (cp - 36) % 7; pos = (cp - 36) / 7; }
  const int ti1 = cp >> 2, tj1 = 2 * (cp & 3) + cm;
  const int tiA = 2 * (dom >> 1) + cm, tjA = (dom & 1) * 4 + pos;
  const int rtB = 2 * dom + cm, jjB = pos;
  const uint32_t bar_full = sbase + SM_BAR, bar_empty = sbase + SM_BAR + NST * 8;
  const uint32_t bar_epoch = sbase + SM_EBAR, bar_kv = sbase + SM_KBAR, bar_pass = sbase + SM_PBAR, bar_pub = sbase + SM_UBAR;

  if (tid == 256) {
    asm volatile("prefetch.tensormap [%0];" ::"l"((uint64_t)&tm_x) : "memory");
    asm volatile("prefetch.tensormap [%0];" ::"l"((uint64_t)&tm_qkv) : "memory");
    asm volatile("prefetch.tensormap [%0];" ::"l"((uint64_t)&tm_wo) : "memory");
    asm volatile("prefetch.tensormap [%0];" ::"l"((uint64_t)&tm_down64) : "memory");
    asm volatile("prefetch.tensormap [%0];" ::"l"((uint64_t)&tm_down48) : "memory");
  }
  if (tid == 0) {
    for (int s = 0; s < NST; ++s) {
      mbar_init(bar_full + s * 8, 1);
      mbar_init(bar_empty + s * 8, 4);
    }
    mbar_init(bar_epoch, 1);
    mbar_init(bar_kv, 1);
    for (int p = 0; p < 6; ++p) mbar_init(bar_pass + p * 8, 1);
    for (int p = 0; p < 8; ++p) mbar_init(bar_pub + p * 8, 4);
    asm volatile("fence.mbarrier_init.release.cluster;" ::: "memory");
  }
  __syncthreads();
  asm volatile("barrier.cluster.arrive.relaxed.aligned;" ::: "memory");

  if (warp >= 8) {
    asm volatile("setmaxnreg.dec.sync.aligned.u32 40;");
    const int pw = warp - 8;
    if (pw == 2 && lane == 0) {
      uint32_t e;
      asm volatile("ld.relaxed.gpu.global.u32 %0, [%1];" : "=r"(e) : "l"(&g_epoch) : "memory");
      *reinterpret_cast<volatile uint32_t*>(smem + SM_MISC) = e;
      mbar_arrive(bar_epoch);
    }
    asm volatile("barrier.cluster.wait.aligned;" ::: "memory");
    if (pw < 2) {
      if (lane == 0) {
        bool gu_ready = false;
#pragma unroll 1
        for (int n = pw; n < NSTAGES; n += 2) {
          const int st = n % NST;
          const uint32_t fb = bar_full + st * 8, dst = sbase + st * STAGE_BYTES;
          if (n >= NST) mbar_wait(bar_empty + st * 8, ((n / NST) - 1) & 1);
          if (n == N_KV + pw) mbar_wait(bar_full + (N_X + 4 + pw) * 8, 0);
          const bool short_tile = n >= N_DN + 8;
          mbar_expect_tx(fb, short_tile ? 12288 : STAGE_BYTES);
          if (n >= N_KV && n < N_WO) {
            if (n < N_Q) {
              tma_3d(dst, &tm_qkv, fb, 64 * (n - N_KV), 8 + tj1);
              tma_3d(dst + 8192, &tm_qkv, fb, 64 * (n - N_KV), 16 + tj1);
            } else {
              tma_3d(dst, &tm_qkv, fb, 128 * (n - N_Q), tj1);
              tma_3d(dst + 8192, &tm_qkv, fb, 128 * (n - N_Q) + 64, tj1);
            }
            continue;
          }
          if (pw != cm) continue;
          if (n < N_KV) {
            tma_3d_mc(dst, &tm_x, fb, (2 * ti1 + (n & 1)) * 64, 2 * (n >> 1));
          } else if (n < N_GU) {
            const int r = n - N_WO;
            tma_3d_mc(dst, &tm_wo, fb, 64 * ((r >> 1) + 4 * (r & 1)), 2 * jjB);
          } else if (n < N_DN) {
            if (!gu_ready) {
              mbar_wait(bar_kv, 0);
              asm volatile("fence.proxy.async.global;" ::: "memory");
              gu_ready = true;
            }
            bulk_g2s_mc(dst, g_wgu + (size_t)(tjA * 24 + (n - N_GU)) * 1024, STAGE_BYTES, fb);
          } else {
            const int u = n - N_DN;
            if (short_tile) {
              tma_3d_mc(dst, &tm_down48, fb, 176 * (2 * (u - 8)) + 128, tjA);
              tma_3d_mc(dst + 8192, &tm_down48, fb, 176 * (2 * (u - 8) + 1) + 128, tjA);
            } else {
              tma_3d_mc(dst, &tm_down64, fb, 176 * (2 * (u & 3)) + 64 * (u >> 2), tjA);
              tma_3d_mc(dst + 8192, &tm_down64, fb, 176 * (2 * (u & 3) + 1) + 64 * (u >> 2), tjA);
            }
          }
        }
      }
      __syncwarp();
    } else {
      const int wg = pw - 2;
      mbar_wait(bar_epoch, 0);
      const uint32_t tag = *reinterpret_cast<volatile uint32_t*>(smem + SM_MISC) + 1;
      {
        const int tjB = 2 * jjB + wg;
#pragma unroll 1
        for (int w = 0; w < 4; ++w) {
          const int slab1 = (2 * ti1 + wg) * 4 + w, slabB = rtB * 4 + w;
#pragma unroll
          for (int q = 0; q < 4; ++q) {
            g_h[(slabB * 32 + 4 * tjB + q) * 32 + lane] = make_uint4(POISON, POISON, POISON, POISON);
            g_pq[tag & 1][(slab1 * 32 + 4 * tj1 + q) * 32 + lane] = make_uint4(0, 0, 0, 0);
          }
          if (lane < 16) reinterpret_cast<uint2*>(g_hstat)[(slabB * 16 + lane) * 8 + tjB] = make_uint2(POISON, POISON);
        }
      }
      asm volatile("bar.sync 9, 64;" ::: "memory");
      if (wg == 0) {
#pragma unroll 1
        for (int v = 0; v < 2; ++v) {
          mbar_wait(bar_pub + v * 8, 0);
          if (lane == 0) asm volatile("red.release.gpu.global.add.u32 [%0], 1;" ::"l"(&g_kvcnt[tj1 * 32]) : "memory");
        }
        const uint32_t target = 32u * tag;
#pragma unroll 1
        for (int it = 0; it < SPIN_LIMIT; ++it) {
          uint32_t v = target;
          if (lane < 8) v = ld_acquire(&g_kvcnt[lane * 32]);
          if (__all_sync(0xffffffffu, (int)(v - target) >= 0)) break;
        }
        __syncwarp();
        if (lane == 0) mbar_arrive(bar_kv);
#pragma unroll 1
        for (int pv = 0; pv < 6; ++pv) {
          const int p = pv >> 1, v = pv & 1;
          mbar_wait(bar_pub + (2 + pv) * 8, 0);
          if (lane == 0) asm volatile("st.release.gpu.global.u32 [%0], %1;" ::"l"(&g_hhflag[((2 * tiA + v) * 3 + p) * 8 + tjA]), "r"(tag) : "memory");
        }
      } else {
        mbar_wait(bar_kv, 0);
#pragma unroll 1
        for (int pv = 0; pv < 6; ++pv) {
          const uint32_t* f = &g_hhflag[((2 * tiA + (pv & 1)) * 3 + (pv >> 1)) * 8 + (lane & 7)];
#pragma unroll 1
          for (int it = 0; it < SPIN_LIMIT; ++it) {
            if (__all_sync(0xffffffffu, ld_acquire(f) == tag)) break;
            __nanosleep(100);
          }
          __syncwarp();
          if (lane == 0) mbar_arrive(bar_pass + pv * 8);
        }
      }
    }
  } else {
    asm volatile("setmaxnreg.inc.sync.aligned.u32 232;");
    const int wg = warp >> 2, w = warp & 3;
    const int g = lane >> 2, t = lane & 3;
    const int tw = tid & 127;
    const uint32_t stage = sbase + SM_STAGE + wg * 16384;
    const uint32_t dlo = ((sbase & 0x3FFFFu) >> 4) | ((8192u >> 4) << 16);
    const int slab1 = (2 * ti1 + wg) * 4 + w;
    const int slabA = (2 * tiA + wg) * 4 + w, rowA = slabA * 16 + g;
    const int slabB = rtB * 4 + w, rowB = slabB * 16 + g, tjB = 2 * jjB + wg;
    auto wait_stage = [&](int n) { mbar_wait(bar_full + (n % NST) * 8, (n / NST) & 1); };
    auto wg_wait1 = [&]() { wgmma_wait<1>(); };
    auto rel_stage = [&](int n, int weight) {
      if (tw < 2) mbar_arrive_cluster(bar_empty + (n % NST) * 8, tw, weight);
    };
    auto desc_at = [&](int n, int off) { return make_desc(dlo + (n % NST) * (STAGE_BYTES >> 4) + (off >> 4)); };
    auto order_wait = [&]() { asm volatile("bar.sync %0, 256;" ::"r"(7 + wg) : "memory"); };
    auto order_arrive = [&]() { asm volatile("bar.arrive %0, 256;" ::"r"(8 - wg) : "memory"); };
    if (wg == 1) order_arrive();
    auto publish = [&](int ev) { __syncwarp(); if (lane == 0) mbar_arrive(bar_pub + (2 * ev + wg) * 8); };

    uint32_t a[32][4];
    float r0, r1;
    {
      uint4 rp[6];
      {
        const __nv_bfloat16* src = ((b >> 6) ? prm.w_up : prm.w_gate) + (size_t)(64 * ((b >> 3) & 7)) * FF + 176 * (b & 7);
        const int nch = ((b & 7) == 7) ? 18 : 22;
#pragma unroll
        for (int u = 0; u < 6; ++u) {
          const int idx = u * 256 + tid;
          const int r = idx / 22, cc = idx - r * 22;
          rp[u] = make_uint4(0, 0, 0, 0);
          if (idx < 1408 && cc < nch) rp[u] = ldg_nc(reinterpret_cast<const uint4*>(src + (size_t)r * FF + cc * 8));
        }
      }
      asm volatile("barrier.cluster.wait.aligned;" ::: "memory");
      float s[2][4] = {}, q1[2][4] = {}, q2[2][4] = {};
      float f0 = 0.f, f1 = 0.f, f2 = 0.f, f3 = 0.f;
      constexpr uint32_t ONES = 0x3F803F80u;
#pragma unroll
      for (int c = 0; c < 4; ++c) {
        const int n = N_X + 2 * c + wg;
        wait_stage(n);
        const int xrow = w * 16 + ((lane >> 3) & 1) * 8 + (lane & 7);
        const uint32_t xs = sbase + (n % NST) * STAGE_BYTES + xrow * 128;
#pragma unroll
        for (int kk = 0; kk < 8; ++kk) {
          const int k = 8 * c + kk;
          ldmatrix_x4(xs + (kk >> 2) * 8192 + (((2 * (kk & 3) + (lane >> 4)) ^ (xrow & 7)) << 4), a[k][0], a[k][1], a[k][2], a[k][3]);
          mma16816(s[kk & 1], a[k][0], a[k][1], a[k][2], a[k][3], ONES, ONES);
          if (kk & 1) {
            f0 = fmaf(bf_lo(a[k][0]), bf_lo(a[k][0]), f0); f0 = fmaf(bf_hi(a[k][0]), bf_hi(a[k][0]), f0);
            f1 = fmaf(bf_lo(a[k][1]), bf_lo(a[k][1]), f1); f1 = fmaf(bf_hi(a[k][1]), bf_hi(a[k][1]), f1);
            f2 = fmaf(bf_lo(a[k][2]), bf_lo(a[k][2]), f2); f2 = fmaf(bf_hi(a[k][2]), bf_hi(a[k][2]), f2);
            f3 = fmaf(bf_lo(a[k][3]), bf_lo(a[k][3]), f3); f3 = fmaf(bf_hi(a[k][3]), bf_hi(a[k][3]), f3);
          } else {
            mma16816(q1[(kk >> 1) & 1], a[k][0], a[k][1], a[k][2], a[k][3], a[k][0], a[k][2]);
            mma16816(q2[(kk >> 1) & 1], a[k][0], a[k][1], a[k][2], a[k][3], a[k][1], a[k][3]);
          }
        }
        named_bar(1 + wg);
        rel_stage(n, 2);
      }
      const int srcl = g * 4 + (g >> 1);
      f0 += f2; f1 += f3;
      f0 += __shfl_xor_sync(0xffffffffu, f0, 1); f1 += __shfl_xor_sync(0xffffffffu, f1, 1);
      f0 += __shfl_xor_sync(0xffffffffu, f0, 2); f1 += __shfl_xor_sync(0xffffffffu, f1, 2);
      const float ssq0 = f0 + __shfl_sync(0xffffffffu, (g & 1) ? q1[0][1] + q1[1][1] : q1[0][0] + q1[1][0], srcl);
      const float ssq1 = f1 + __shfl_sync(0xffffffffu, (g & 1) ? q2[0][3] + q2[1][3] : q2[0][2] + q2[1][2], srcl);
      const float mean0 = (s[0][0] + s[1][0]) * (1.0f / DM), mean1 = (s[0][2] + s[1][2]) * (1.0f / DM);
      const float var0 = fmaxf(ssq0 * (1.0f / DM) - mean0 * mean0, 0.f);
      const float var1 = fmaxf(ssq1 * (1.0f / DM) - mean1 * mean1, 0.f);
      uint32_t m0, m1;
      ln_params(mean0, var0, m0, r0);
      ln_params(mean1, var1, m1, r1);
#pragma unroll
      for (int k = 0; k < 32; ++k) {
        a[k][0] = hsub2_bf16(a[k][0], m0);
        a[k][1] = hsub2_bf16(a[k][1], m1);
        a[k][2] = hsub2_bf16(a[k][2], m0);
        a[k][3] = hsub2_bf16(a[k][3], m1);
      }
      {
        uint4* dst = g_wgu + (size_t)(((b & 7) * 24 + ((b >> 3) & 7)) * 2 + (b >> 6)) * 512;
        const int nch = ((b & 7) == 7) ? 18 : 22;
#pragma unroll
        for (int u = 0; u < 6; ++u) {
          const int idx = u * 256 + tid;
          const int r = idx / 22, cc = idx - r * 22;
          if (idx < 1408 && cc < nch) dst[(cc >> 3) * 8 * 1024 + r * 8 + ((cc & 7) ^ (r & 7))] = rp[u];
        }
      }
    }
    mbar_wait(bar_epoch, 0);
    const uint32_t epoch = *reinterpret_cast<volatile uint32_t*>(smem + SM_MISC);
    const uint32_t tag = epoch + 1;
    const int par = epoch & 1;
    const uint4* hhsrc = g_hh + slabA * 88 * 32 + lane;
    auto load_group = [&](int slot, int n) {
      const int p = n >> 3;
      const uint4* s = hhsrc + (11 * (n & 7) + 4 * p) * 32;
#pragma unroll
      for (int ks = 0; ks < 4; ++ks) {
        if (ks < 3 || p < 2) {
          const uint4 v = ldg_cg(s + ks * 32);
          a[4 * slot + ks][0] = v.x; a[4 * slot + ks][1] = v.y; a[4 * slot + ks][2] = v.z; a[4 * slot + ks][3] = v.w;
        }
      }
    };
    auto wait_pass = [&](int p) { mbar_wait(bar_pass + (2 * p + wg) * 8, 0); };
    auto gemm_k512 = [&](float (&acc)[64], int n0, auto narrow, auto prep) {
      asm volatile("" : "+r"(n0));
      int st = n0 % NST, ph = (n0 / NST) & 1, prev = 0;
#pragma unroll
      for (int kt = 0; kt < 8; ++kt) {
        prep(kt);
        if ((kt & 3) == 0) order_wait();
        { mbar_wait(bar_full + st * 8, ph); }
        wgmma_fence();
        const uint32_t d0 = dlo + st * (STAGE_BYTES >> 4);
#pragma unroll
        for (int ks = 0; ks < 4; ++ks) {
          const int k = 4 * kt + ks;
          if constexpr (decltype(narrow)::value)
            wgmma_rs_n112(*reinterpret_cast<float (*)[56]>(&acc[0]), a[k][0], a[k][1], a[k][2], a[k][3], make_desc(d0 + ks * 128), k > 0);
          else
            wgmma_rs_n128(acc, a[k][0], a[k][1], a[k][2], a[k][3], make_desc(d0 + ks * 128), k > 0);
        }
        wgmma_commit();
        if ((kt & 3) == 3 && !(decltype(narrow)::value && kt == 7 && wg == 1)) order_arrive();
        if (kt > 0) {
          wg_wait1();
          if (tw < 2) mbar_arrive_cluster(bar_empty + prev * 8, tw, 1);
          if constexpr (decltype(narrow)::value) {
            if (kt == 1) wait_pass(0);
            load_group(kt - 1, kt - 1);
          }
        }
        prev = st;
        if (++st == NST) { st = 0; ph ^= 1; }
      }
      wgmma_wait<0>();
      if (tw < 2) mbar_arrive_cluster(bar_empty + prev * 8, tw, 1);
      if constexpr (decltype(narrow)::value) load_group(7, 7);
    };
    {
      float acc[64];
      gemm_k512(acc, N_KV, std::false_type{}, [](int) {});
      {
        const int mrow = w * 16 + ((lane >> 3) & 1) * 8 + (lane & 7);
        const int mch = lane >> 4;
#pragma unroll
        for (int hh = 0; hh < 4; ++hh) {
          const uint32_t off = mrow * 128 + (((2 * hh + mch) ^ (mrow & 7)) << 4);
          stmatrix_x4(stage + off, phi_pack(acc[8 * hh + 0] * r0, acc[8 * hh + 1] * r0), phi_pack(acc[8 * hh + 2] * r1, acc[8 * hh + 3] * r1),
                      phi_pack(acc[8 * hh + 4] * r0, acc[8 * hh + 5] * r0), phi_pack(acc[8 * hh + 6] * r1, acc[8 * hh + 7] * r1));
          stmatrix_x4(stage + 8192 + off, pack_bf16(acc[32 + 8 * hh + 0] * r0, acc[32 + 8 * hh + 1] * r0),
                      pack_bf16(acc[32 + 8 * hh + 2] * r1, acc[32 + 8 * hh + 3] * r1),
                      pack_bf16(acc[32 + 8 * hh + 4] * r0, acc[32 + 8 * hh + 5] * r0),
                      pack_bf16(acc[32 + 8 * hh + 6] * r1, acc[32 + 8 * hh + 7] * r1));
        }
      }
      named_bar(1 + wg);
    }
    {
      constexpr uint32_t ONES = 0x3F803F80u;
      float d0[4] = {}, d1[4] = {}, z0[4] = {}, z1[4] = {};
#pragma unroll
      for (int ks = 0; ks < 4; ++ks) {
        uint32_t va0, va1, va2, va3, pb0, pb1, pb2, pb3;
        {
          const int r = 16 * ks + (lane >> 4) * 8 + (lane & 7);
          const int ch = 2 * w + ((lane >> 3) & 1);
          ldmatrix_x4_trans(stage + 8192 + r * 128 + ((ch ^ (r & 7)) << 4), va0, va1, va2, va3);
        }
        {
          const int r = 16 * ks + ((lane >> 3) & 1) * 8 + (lane & 7);
          const int ch = 2 * w + (lane >> 4);
          ldmatrix_x4_trans(stage + r * 128 + ((ch ^ (r & 7)) << 4), pb0, pb1, pb2, pb3);
        }
        mma16816(d0, va0, va1, va2, va3, pb0, pb1);
        mma16816(d1, va0, va1, va2, va3, pb2, pb3);
        mma16816(z0, ONES, ONES, ONES, ONES, pb0, pb1);
        mma16816(z1, ONES, ONES, ONES, ONES, pb2, pb3);
      }
      const int head = 4 * tj1 + w;
      float4* kvp = &g_kv[par][(head * 32 + lane) * 2];
      red_add_v4(kvp, d0[0], d0[1], d1[0], d1[1]);
      red_add_v4(kvp + 1, d0[2], d0[3], d1[2], d1[3]);
      if (g == 0) red_add_v4(&g_z[par][head * 4 + t], z0[0], z0[1], z1[0], z1[1]);
      asm volatile("fence.proxy.async.global;" ::: "memory");
      publish(0);
    }
    {
      {
        float accq[32];
        order_wait();
#pragma unroll
        for (int kt = 0; kt < 8; ++kt) {
          if ((kt & 1) == 0) wait_stage(N_Q + (kt >> 1));
          wgmma_fence();
#pragma unroll
          for (int ks = 0; ks < 4; ++ks) {
            const int k = 4 * kt + ks;
            wgmma_rs_n64(accq, a[k][0], a[k][1], a[k][2], a[k][3], desc_at(N_Q + (kt >> 1), (kt & 1) * 8192 + ks * 2048), k > 0);
          }
          wgmma_commit();
          if (kt == 7) order_arrive();
          if (kt > 0) {
            wg_wait1();
            if ((kt & 1) == 0) rel_stage(N_Q + (kt >> 1) - 1, 1);
          }
        }
        wgmma_wait<0>();
        rel_stage(N_Q + 3, 1);
#pragma unroll
        for (int hh = 0; hh < 4; ++hh)
          st_x(&g_pq[par][(slab1 * 32 + 4 * tj1 + hh) * 32 + lane], phi_pack(accq[8 * hh + 0] * r0, accq[8 * hh + 1] * r0),
               phi_pack(accq[8 * hh + 2] * r1, accq[8 * hh + 3] * r1), phi_pack(accq[8 * hh + 4] * r0, accq[8 * hh + 5] * r0),
               phi_pack(accq[8 * hh + 6] * r1, accq[8 * hh + 7] * r1));
      }
      if (b < 32) {
        g_kv[par ^ 1][b * 64 + (tid & 63)] = make_float4(0.f, 0.f, 0.f, 0.f);
        if (tid < 4) g_z[par ^ 1][b * 4 + tid] = make_float4(0.f, 0.f, 0.f, 0.f);
      }
    }

    auto cross_reduce = [&](float (&acc)[64], float (&out)[32]) {
      float4* mine = reinterpret_cast<float4*>(smem + SM_STAGE + wg * 16384) + tw;
      const float4* theirs = reinterpret_cast<const float4*>(smem + SM_STAGE + (wg ^ 1) * 16384) + tw;
#pragma unroll
      for (int i = 0; i < 8; ++i)
        mine[i * 128] = wg ? make_float4(acc[4 * i], acc[4 * i + 1], acc[4 * i + 2], acc[4 * i + 3])
                           : make_float4(acc[32 + 4 * i], acc[32 + 4 * i + 1], acc[32 + 4 * i + 2], acc[32 + 4 * i + 3]);
      asm volatile("bar.sync 4, 256;" ::: "memory");
#pragma unroll
      for (int i = 0; i < 8; ++i) {
        const float4 v = theirs[i * 128];
        out[4 * i + 0] = (wg ? acc[32 + 4 * i + 0] : acc[4 * i + 0]) + v.x;
        out[4 * i + 1] = (wg ? acc[32 + 4 * i + 1] : acc[4 * i + 1]) + v.y;
        out[4 * i + 2] = (wg ? acc[32 + 4 * i + 2] : acc[4 * i + 2]) + v.z;
        out[4 * i + 3] = (wg ? acc[32 + 4 * i + 3] : acc[4 * i + 3]) + v.w;
      }
    };

    {
      uint32_t xr[4][4];
#pragma unroll
      for (int q = 0; q < 4; ++q) {
        const uint32_t* p0 = reinterpret_cast<const uint32_t*>(prm.x + (size_t)rowB * DM + 64 * tjB + 16 * q + 2 * t);
        xr[q][0] = __ldg(p0);
        xr[q][1] = __ldg(p0 + 8 * DM / 2);
        xr[q][2] = __ldg(p0 + 4);
        xr[q][3] = __ldg(p0 + 8 * DM / 2 + 4);
      }
      const uint4* osrc = &g_pq[par][(slabB * 32 + 16 * wg) * 32];
      uint4 of[16];
      poll_sources<0u>(osrc, 4, 3, lane);
      fetch<16>(of, osrc + lane);
      mbar_wait(bar_kv, 0);
      if (b == 0 && tid == 0) asm volatile("st.relaxed.gpu.global.u32 [%0], %1;" ::"l"(&g_epoch), "r"(tag) : "memory");
      {
#pragma unroll
        for (int it = 0; it < 4; ++it) {
          const int e = (16 * wg) * 32 + tw + 128 * it;
          const float4 lo = ldg_cg_f4(&g_kv[par][e * 2]), hi = ldg_cg_f4(&g_kv[par][e * 2 + 1]);
          *reinterpret_cast<uint4*>(smem + SM_STAGE + wg * 16384 + (tw + 128 * it) * 16) =
              make_uint4(pack_bf16(lo.x, lo.y), pack_bf16(lo.z, lo.w), pack_bf16(hi.x, hi.y), pack_bf16(hi.z, hi.w));
        }
        if (tw < 64) {
          const float4 zz = ldg_cg_f4(&g_z[par][64 * wg + tw]);
          *reinterpret_cast<uint2*>(smem + SM_STAGE + wg * 16384 + 8192 + tw * 8) = make_uint2(pack_bf16(zz.x, zz.y), pack_bf16(zz.z, zz.w));
        }
      }
      named_bar(1 + wg);
      float acc[64];
#pragma unroll
      for (int n = 0; n < 4; ++n) {
        const int sn = N_WO + 2 * n + wg;
        { ensure<4, 0u>(&of[4 * n], osrc + lane + 4 * n * 32); }
#pragma unroll
        for (int ks = 0; ks < 4; ++ks) {
          const int hl = 4 * n + ks;
          const uint4 kf = *reinterpret_cast<const uint4*>(smem + SM_STAGE + wg * 16384 + (hl * 32 + lane) * 16);
          const uint2 zf = *reinterpret_cast<const uint2*>(smem + SM_STAGE + wg * 16384 + 8192 + (hl * 4 + t) * 8);
          uint4& p = of[hl];
          float n0[4] = {}, n1[4] = {}, dn[4] = {};
          mma16816(dn, p.x, p.y, p.z, p.w, zf.x, zf.y);
          mma16816(n0, p.x, p.y, p.z, p.w, kf.x, kf.y);
          mma16816(n1, p.x, p.y, p.z, p.w, kf.z, kf.w);
          const float i0 = rcp_approx(dn[0] + 1e-6f), i1 = rcp_approx(dn[2] + 1e-6f);
          p = make_uint4(pack_bf16(n0[0] * i0, n0[1] * i0), pack_bf16(n0[2] * i1, n0[3] * i1), pack_bf16(n1[0] * i0, n1[1] * i0),
                         pack_bf16(n1[2] * i1, n1[3] * i1));
        }
        wait_stage(sn);
        wgmma_fence();
#pragma unroll
        for (int ks = 0; ks < 4; ++ks)
          wgmma_rs_n128(acc, of[4 * n + ks].x, of[4 * n + ks].y, of[4 * n + ks].z, of[4 * n + ks].w, desc_at(sn, ks * 2048), (n | ks) > 0);
        wgmma_commit();
        if (n > 0) {
          wg_wait1();
          rel_stage(sn - 2, 2);
        }
      }
      wgmma_wait<0>();
      rel_stage(N_WO + 6 + wg, 2);
      named_bar(1 + wg);
      float sum[32];
      cross_reduce(acc, sum);

      uint32_t hf[4][4];
      float s0 = 0.f, s1 = 0.f;
#pragma unroll
      for (int q = 0; q < 4; ++q) {
#pragma unroll
        for (int r = 0; r < 4; ++r) {
          hf[q][r] = hadd2_bf16(xr[q][r], pack_bf16(sum[8 * q + 2 * r], sum[8 * q + 2 * r + 1]));
          const float sv = bf_lo(hf[q][r]) + bf_hi(hf[q][r]);
          if (r & 1) s1 += sv; else s0 += sv;
        }
        st_x(g_h + (slabB * 32 + 4 * tjB + q) * 32 + lane, hf[q][0], hf[q][1], hf[q][2], hf[q][3]);
      }
      s0 += __shfl_xor_sync(0xffffffffu, s0, 1); s1 += __shfl_xor_sync(0xffffffffu, s1, 1);
      s0 += __shfl_xor_sync(0xffffffffu, s0, 2); s1 += __shfl_xor_sync(0xffffffffu, s1, 2);
      const float mu0 = s0 * (1.0f / 64), mu1 = s1 * (1.0f / 64);
      float e0 = 0.f, e1 = 0.f;
#pragma unroll
      for (int q = 0; q < 4; ++q) {
#pragma unroll
        for (int r = 0; r < 4; ++r) {
          const float mu = (r & 1) ? mu1 : mu0;
          const float dl = bf_lo(hf[q][r]) - mu, dh = bf_hi(hf[q][r]) - mu;
          const float sv = dl * dl + dh * dh;
          if (r & 1) e1 += sv; else e0 += sv;
        }
      }
      e0 += __shfl_xor_sync(0xffffffffu, e0, 1); e1 += __shfl_xor_sync(0xffffffffu, e1, 1);
      e0 += __shfl_xor_sync(0xffffffffu, e0, 2); e1 += __shfl_xor_sync(0xffffffffu, e1, 2);
      if (t < 2) {
        const uint64_t pk = t == 0 ? ((uint64_t)__float_as_uint(e0) << 32 | __float_as_uint(mu0)) : ((uint64_t)__float_as_uint(e1) << 32 | __float_as_uint(mu1));
        const uint64_t* dst = reinterpret_cast<const uint64_t*>(g_hstat) + (rowB + 8 * t) * 8 + tjB;
        asm volatile("st.relaxed.gpu.global.u64 [%0], %1;" ::"l"(dst), "l"(pk) : "memory");
      }
    }

    {
      const uint4* hsrc = g_h + slabA * 32 * 32;
      uint32_t m0, m1;
      {
#pragma unroll 1
        for (int it = 0; it < SPIN_LIMIT; ++it) {
          const uint4 q = ld_x(&g_hstat[slabA * 64 + t]);
          if (!__any_sync(0xffffffffu, q.x == POISON || q.z == POISON)) break;
        }
        uint4 p0 = ld_x(&g_hstat[rowA * 4 + t]), p1 = ld_x(&g_hstat[(rowA + 8) * 4 + t]);
#pragma unroll
        for (int k = 0; k < 32; ++k) {
          const uint4 v = ld_x(hsrc + lane + k * 32);
          a[k][0] = v.x; a[k][1] = v.y; a[k][2] = v.z; a[k][3] = v.w;
        }
#pragma unroll 1
        for (int it = 0; it < SPIN_LIMIT; ++it) {
          if (!__any_sync(0xffffffffu, p0.x == POISON || p0.z == POISON || p1.x == POISON || p1.z == POISON)) break;
          p0 = ld_x(&g_hstat[rowA * 4 + t]);
          p1 = ld_x(&g_hstat[(rowA + 8) * 4 + t]);
        }
        const float a0x = __uint_as_float(p0.x), a0y = __uint_as_float(p0.y), a0z = __uint_as_float(p0.z), a0w = __uint_as_float(p0.w);
        const float a1x = __uint_as_float(p1.x), a1y = __uint_as_float(p1.y), a1z = __uint_as_float(p1.z), a1w = __uint_as_float(p1.w);
        float a0 = a0x + a0z, a1 = a1x + a1z;
        a0 += __shfl_xor_sync(0xffffffffu, a0, 1); a1 += __shfl_xor_sync(0xffffffffu, a1, 1);
        a0 += __shfl_xor_sync(0xffffffffu, a0, 2); a1 += __shfl_xor_sync(0xffffffffu, a1, 2);
        const float mean0 = a0 * 0.125f, mean1 = a1 * 0.125f;
        float v0 = a0y + a0w + 64.f * ((a0x - mean0) * (a0x - mean0) + (a0z - mean0) * (a0z - mean0));
        float v1 = a1y + a1w + 64.f * ((a1x - mean1) * (a1x - mean1) + (a1z - mean1) * (a1z - mean1));
        v0 += __shfl_xor_sync(0xffffffffu, v0, 1); v1 += __shfl_xor_sync(0xffffffffu, v1, 1);
        v0 += __shfl_xor_sync(0xffffffffu, v0, 2); v1 += __shfl_xor_sync(0xffffffffu, v1, 2);
        ln_params(mean0, v0 * (1.0f / DM), m0, r0);
        ln_params(mean1, v1 * (1.0f / DM), m1, r1);
      }
      auto prep_h = [&](int kt) {
        if (__builtin_expect(__any_sync(0xffffffffu, a[4 * kt][0] == POISON || a[4 * kt + 1][0] == POISON || a[4 * kt + 2][0] == POISON || a[4 * kt + 3][0] == POISON), 0)) {
#pragma unroll 1
          for (int it = 0; it < SPIN_LIMIT; ++it) {
            uint4 v[4];
            fetch<4>(v, hsrc + lane + 4 * kt * 32);
#pragma unroll
            for (int ks = 0; ks < 4; ++ks) { a[4 * kt + ks][0] = v[ks].x; a[4 * kt + ks][1] = v[ks].y; a[4 * kt + ks][2] = v[ks].z; a[4 * kt + ks][3] = v[ks].w; }
            if (!any_poison<4>(v)) break;
          }
        }

#pragma unroll
        for (int ks = 0; ks < 4; ++ks) {
          a[4 * kt + ks][0] = hsub2_bf16(a[4 * kt + ks][0], m0);
          a[4 * kt + ks][1] = hsub2_bf16(a[4 * kt + ks][1], m1);
          a[4 * kt + ks][2] = hsub2_bf16(a[4 * kt + ks][2], m0);
          a[4 * kt + ks][3] = hsub2_bf16(a[4 * kt + ks][3], m1);
        }
      };
#pragma unroll 1
      for (int p = 0; p < 3; ++p) {
        float acc[64];
        if (p == 0) gemm_k512(acc, N_GU + 8 * p, std::false_type{}, prep_h);
        else if (p == 1) gemm_k512(acc, N_GU + 8 * p, std::false_type{}, [](int) {});
        else gemm_k512(acc, N_GU + 8 * p, std::true_type{}, [](int) {});
#pragma unroll
        for (int qq = 0; qq < 4; ++qq) {
          if (qq < 3 || p < 2) {
            uint32_t v[4];
#pragma unroll
            for (int r = 0; r < 4; ++r) {
              const float sc = (r & 1) ? r1 : r0;
              v[r] = hmul2_bf16(pack_bf16(acc[8 * qq + 2 * r] * sc, acc[8 * qq + 2 * r + 1] * sc),
                                pack_bf16(acc[32 + 8 * qq + 2 * r] * sc, acc[32 + 8 * qq + 2 * r + 1] * sc));
            }
            g_hh[(slabA * 88 + 11 * tjA + 4 * p + qq) * 32 + lane] = make_uint4(v[0], v[1], v[2], v[3]);
          }
        }
        publish(1 + p);
      }
    }

    {
      float sum[32];
      uint32_t dl4 = dlo;
      asm volatile("" : "+r"(dl4));
#pragma unroll
      for (int n = 0; n < 24; ++n) {
        const int sn = N_DN + (n >> 1), sl = n & 7;
        if ((n & 1) == 0) wait_stage(sn);
        wgmma_fence();
#pragma unroll
        for (int ks = 0; ks < 4; ++ks)
          if (ks < 3 || n < 16)
            wgmma_rs_n64(sum, a[4 * sl + ks][0], a[4 * sl + ks][1], a[4 * sl + ks][2], a[4 * sl + ks][3], make_desc(dl4 + (sn % NST) * (STAGE_BYTES >> 4) + (((n & 1) * 8192 + ks * 2048) >> 4)), (n | ks) > 0);
        wgmma_commit();
        if (n > 0) {
          wg_wait1();
          if (n == 1) wait_pass(1);
          if (n == 9) wait_pass(2);
          if (n - 1 + 8 < 24) load_group((n - 1) & 7, n - 1 + 8);
        }
      }
      uint4 hf[4];
#pragma unroll
      for (int q = 0; q < 4; ++q) hf[q] = ldg_cg(&g_h[(slabA * 32 + 4 * tjA + q) * 32 + lane]);
      wgmma_wait<0>();
      const uint32_t wst = stage + w * 2048;
      {
        const int mrow = ((lane >> 3) & 1) * 8 + (lane & 7);
        const int mch = lane >> 4;
#pragma unroll
        for (int q = 0; q < 4; ++q) {
          stmatrix_x4(wst + mrow * 128 + (((2 * q + mch) ^ (mrow & 7)) << 4),
                      hadd2_bf16(hf[q].x, pack_bf16(sum[8 * q + 0], sum[8 * q + 1])), hadd2_bf16(hf[q].y, pack_bf16(sum[8 * q + 2], sum[8 * q + 3])),
                      hadd2_bf16(hf[q].z, pack_bf16(sum[8 * q + 4], sum[8 * q + 5])), hadd2_bf16(hf[q].w, pack_bf16(sum[8 * q + 6], sum[8 * q + 7])));
        }
      }
      __syncwarp();
#pragma unroll
      for (int it = 0; it < 4; ++it) {
        const int r = it * 4 + (lane >> 3), ch = lane & 7;
        uint4 v;
        asm volatile("ld.shared.v4.u32 {%0,%1,%2,%3}, [%4];" : "=r"(v.x), "=r"(v.y), "=r"(v.z), "=r"(v.w) : "r"(wst + r * 128 + ((ch ^ (r & 7)) << 4)));
        *reinterpret_cast<uint4*>(prm.out + (size_t)(slabA * 16 + r) * DM + 64 * tjA + ch * 8) = v;
      }
    }
  }
  asm volatile("barrier.cluster.arrive.relaxed.aligned;\nbarrier.cluster.wait.aligned;" ::: "memory");
}

typedef CUresult (*EncodeTiledFn)(CUtensorMap*, CUtensorMapDataType, cuuint32_t, void*, const cuuint64_t*, const cuuint64_t*,
                                  const cuuint32_t*, const cuuint32_t*, CUtensorMapInterleave, CUtensorMapSwizzle,
                                  CUtensorMapL2promotion, CUtensorMapFloatOOBfill);

void encode_blk(EncodeTiledFn enc, CUtensorMap* tm, const void* p, int rows, int cols, int box_rows, int box_blks) {
  cuuint64_t gd[3] = {64, (cuuint64_t)rows, (cuuint64_t)cols / 64};
  cuuint64_t gs[2] = {(cuuint64_t)cols * 2, 128};
  cuuint32_t bx[3] = {64, (cuuint32_t)box_rows, (cuuint32_t)box_blks};
  cuuint32_t es[3] = {1, 1, 1};
  enc(tm, CU_TENSOR_MAP_DATA_TYPE_BFLOAT16, 3, const_cast<void*>(p), gd, gs, bx, es, CU_TENSOR_MAP_INTERLEAVE_NONE,
      CU_TENSOR_MAP_SWIZZLE_128B, CU_TENSOR_MAP_L2_PROMOTION_L2_128B, CU_TENSOR_MAP_FLOAT_OOB_FILL_NONE);
}

}

extern "C" void kernel_launch(void* const* d_in, const int* in_sizes, int n_in, void* d_out, int out_size) {
  (void)in_sizes; (void)n_in; (void)out_size;
  static CUtensorMap tm_x, tm_qkv, tm_wo, tm_down64, tm_down48;
  static const void* cached[4] = {nullptr, nullptr, nullptr, nullptr};
  static bool attr_done = false;
  const void* ptrs[4] = {d_in[1], d_in[2], d_in[6], d_in[0]};
  bool same = true;
  for (int i = 0; i < 4; ++i) same = same && (cached[i] == ptrs[i]);
  if (!same) {
    void* fn = nullptr;
    cudaDriverEntryPointQueryResult qr;
    cudaGetDriverEntryPoint("cuTensorMapEncodeTiled", &fn, cudaEnableDefault, &qr);
    EncodeTiledFn enc = (EncodeTiledFn)fn;
    encode_blk(enc, &tm_qkv, ptrs[0], DM, 3 * DM, 64, 1);
    encode_blk(enc, &tm_wo, ptrs[1], DM, DM, 64, 2);
    encode_blk(enc, &tm_down64, ptrs[2], FF, DM, 64, 1);
    encode_blk(enc, &tm_down48, ptrs[2], FF, DM, 48, 1);
    encode_blk(enc, &tm_x, ptrs[3], 2048, DM, 64, 2);
    for (int i = 0; i < 4; ++i) cached[i] = ptrs[i];
  }
  if (!attr_done) {
    cudaFuncSetAttribute(fused_block_kernel, cudaFuncAttributeMaxDynamicSharedMemorySize, SM_TOTAL);
    attr_done = true;
  }
  Params prm;
  prm.x = (const __nv_bfloat16*)d_in[0];
  prm.w_gate = (const __nv_bfloat16*)d_in[4];
  prm.w_up = (const __nv_bfloat16*)d_in[5];
  prm.out = (__nv_bfloat16*)d_out;
  cudaLaunchConfig_t cfg = {};
  cfg.gridDim = dim3(NCTA);
  cfg.blockDim = dim3(384);
  cfg.dynamicSmemBytes = SM_TOTAL;
  cfg.stream = cudaStreamPerThread;
  cudaLaunchAttribute at[1];
  at[0].id = cudaLaunchAttributeClusterDimension;
  at[0].val.clusterDim.x = 2;
  at[0].val.clusterDim.y = 1;
  at[0].val.clusterDim.z = 1;
  cfg.attrs = at;
  cfg.numAttrs = 1;
  cudaLaunchKernelEx(&cfg, fused_block_kernel, tm_x, tm_qkv, tm_wo, tm_down64, tm_down48, prm);
}
```

```cpp
#include <cuda_runtime.h>
#include <cuda_bf16.h>
#include <cuda.h>
#include <stdint.h>
#include <type_traits>

namespace {

constexpr int DM = 512;
constexpr int FF = 1376;
constexpr int NCTA = 128;
constexpr int NST = 12;
constexpr int STAGE_BYTES = 16384;
constexpr int N_X = 0, N_KV = 8, N_Q = 16, N_WO = 20, N_GU = 28, N_DN = 52, NSTAGES = 64;

constexpr int SM_STAGE = NST * STAGE_BYTES;
constexpr int SM_BAR = SM_STAGE + 32768;
constexpr int SM_EBAR = SM_BAR + 2 * NST * 8;
constexpr int SM_KBAR = SM_EBAR + 8;
constexpr int SM_PBAR = SM_KBAR + 8;
constexpr int SM_UBAR = SM_PBAR + 48;
constexpr int SM_MISC = SM_UBAR + 64;
constexpr int SM_ZF = SM_MISC + 16;
constexpr int SM_TOTAL = SM_ZF + 2048;

constexpr int SPIN_LIMIT = 1 << 20;
constexpr uint32_t POISON = 0xFFFFFFFFu;

__device__ uint4 g_pq[2][128 * 32 * 32];
__device__ uint4 g_h[128 * 32 * 32];
__device__ uint4 g_hh[128 * 88 * 32];
__device__ uint4 g_hstat[2048 * 4];
__device__ float4 g_kv[2][32 * 32 * 2];
__device__ float4 g_z[2][32 * 4];
__device__ uint4 g_wgu[8 * 3 * 8 * 2 * 512];
__device__ uint32_t g_hhflag[32 * 3 * 8];
__device__ uint32_t g_kvcnt[8 * 32];
__device__ uint32_t g_epoch;

__device__ __forceinline__ uint32_t smem_u32(const void* p) { return (uint32_t)__cvta_generic_to_shared(p); }
__device__ __forceinline__ void mbar_init(uint32_t bar, uint32_t cnt) {
  asm volatile("mbarrier.init.shared::cta.b64 [%0], %1;" ::"r"(bar), "r"(cnt) : "memory");
}
__device__ __forceinline__ void mbar_expect_tx(uint32_t bar, uint32_t bytes) {
  asm volatile("mbarrier.arrive.expect_tx.shared::cta.b64 _, [%0], %1;" ::"r"(bar), "r"(bytes) : "memory");
}
__device__ __forceinline__ void mbar_arrive(uint32_t bar) {
  asm volatile("mbarrier.arrive.shared::cta.b64 _, [%0];" ::"r"(bar) : "memory");
}
__device__ __forceinline__ void mbar_wait(uint32_t bar, uint32_t parity) {
  asm volatile(
      "{\n.reg .pred p;\n.reg .u32 c;\nmov.u32 c, 0;\n"
      "W%=:\nmbarrier.try_wait.parity.shared::cta.b64 p, [%0], %1;\n@p bra D%=;\n"
      "add.u32 c, c, 1;\nsetp.lt.u32 p, c, %2;\n@p bra W%=;\nD%=:\n}\n" ::"r"(bar), "r"(parity), "n"(SPIN_LIMIT)
      : "memory");
}
__device__ __forceinline__ void tma_3d_mc(uint32_t dst, const CUtensorMap* tm, uint32_t bar, int c1, int c2) {
  asm volatile(
      "cp.async.bulk.tensor.3d.shared::cluster.global.mbarrier::complete_tx::bytes.multicast::cluster [%0], [%1, {%3, %4, %5}], [%2], %6;" ::"r"(dst),
      "l"((uint64_t)tm), "r"(bar), "r"(0), "r"(c1), "r"(c2), "h"((uint16_t)3)
      : "memory");
}
__device__ __forceinline__ void tma_3d(uint32_t dst, const CUtensorMap* tm, uint32_t bar, int c1, int c2) {
  asm volatile(
      "cp.async.bulk.tensor.3d.shared::cluster.global.mbarrier::complete_tx::bytes [%0], [%1, {%3, %4, %5}], [%2];" ::"r"(dst),
      "l"((uint64_t)tm), "r"(bar), "r"(0), "r"(c1), "r"(c2)
      : "memory");
}
__device__ __forceinline__ void bulk_g2s_mc(uint32_t dst, const void* src, uint32_t bytes, uint32_t bar) {
  asm volatile("cp.async.bulk.shared::cluster.global.mbarrier::complete_tx::bytes.multicast::cluster [%0], [%1], %2, [%3], %4;" ::"r"(dst),
               "l"(src), "r"(bytes), "r"(bar), "h"((uint16_t)3)
               : "memory");
}
__device__ __forceinline__ void mbar_arrive_cluster(uint32_t bar, uint32_t rank, uint32_t count) {
  asm volatile(
      "{\n.reg .b32 ra;\nmapa.shared::cluster.u32 ra, %0, %1;\nmbarrier.arrive.shared::cluster.b64 _, [ra], %2;\n}\n" ::"r"(bar), "r"(rank), "r"(count)
      : "memory");
}
__device__ __forceinline__ void wgmma_fence() { asm volatile("wgmma.fence.sync.aligned;" ::: "memory"); }
__device__ __forceinline__ void wgmma_commit() { asm volatile("wgmma.commit_group.sync.aligned;" ::: "memory"); }
template <int N>
__device__ __forceinline__ void wgmma_wait() { asm volatile("wgmma.wait_group.sync.aligned %0;" ::"n"(N) : "memory"); }

__device__ __forceinline__ uint64_t make_desc(uint32_t lo) {
  return (uint64_t)lo | ((uint64_t)((1024u >> 4) | (1u << 30)) << 32);
}

__device__ __forceinline__ void wgmma_rs_n64(float (&d)[32], uint32_t a0, uint32_t a1, uint32_t a2, uint32_t a3, uint64_t descB, int scaleD) {
  asm volatile(
    "{\n.reg .pred p;\nsetp.ne.b32 p, %37, 0;\n"
    "wgmma.mma_async.sync.aligned.m64n64k16.f32.bf16.bf16 "
    "{%0, %1, %2, %3, %4, %5, %6, %7, %8, %9, %10, %11, %12, %13, %14, %15, "
    "%16, %17, %18, %19, %20, %21, %22, %23, %24, %25, %26, %27, %28, %29, %30, %31}, "
    "{%32, %33, %34, %35}, %36, p, 1, 1, 1;\n}\n"
    : "+f"(d[0]), "+f"(d[1]), "+f"(d[2]), "+f"(d[3]), "+f"(d[4]), "+f"(d[5]), "+f"(d[6]), "+f"(d[7]),
      "+f"(d[8]), "+f"(d[9]), "+f"(d[10]), "+f"(d[11]), "+f"(d[12]), "+f"(d[13]), "+f"(d[14]), "+f"(d[15]),
      "+f"(d[16]), "+f"(d[17]), "+f"(d[18]), "+f"(d[19]), "+f"(d[20]), "+f"(d[21]), "+f"(d[22]), "+f"(d[23]),
      "+f"(d[24]), "+f"(d[25]), "+f"(d[26]), "+f"(d[27]), "+f"(d[28]), "+f"(d[29]), "+f"(d[30]), "+f"(d[31])
    : "r"(a0), "r"(a1), "r"(a2), "r"(a3), "l"(descB), "r"(scaleD));
}

__device__ __forceinline__ void wgmma_rs_n112(float (&d)[56], uint32_t a0, uint32_t a1, uint32_t a2, uint32_t a3, uint64_t descB, int scaleD) {
  asm volatile(
    "{\n.reg .pred p;\nsetp.ne.b32 p, %61, 0;\n"
    "wgmma.mma_async.sync.aligned.m64n112k16.f32.bf16.bf16 "
    "{%0, %1, %2, %3, %4, %5, %6, %7, %8, %9, %10, %11, %12, %13, %14, %15, "
    "%16, %17, %18, %19, %20, %21, %22, %23, %24, %25, %26, %27, %28, %29, %30, %31, "
    "%32, %33, %34, %35, %36, %37, %38, %39, %40, %41, %42, %43, %44, %45, %46, %47, "
    "%48, %49, %50, %51, %52, %53, %54, %55}, "
    "{%56, %57, %58, %59}, %60, p, 1, 1, 1;\n}\n"
    : "+f"(d[0]), "+f"(d[1]), "+f"(d[2]), "+f"(d[3]), "+f"(d[4]), "+f"(d[5]), "+f"(d[6]), "+f"(d[7]),
      "+f"(d[8]), "+f"(d[9]), "+f"(d[10]), "+f"(d[11]), "+f"(d[12]), "+f"(d[13]), "+f"(d[14]), "+f"(d[15]),
      "+f"(d[16]), "+f"(d[17]), "+f"(d[18]), "+f"(d[19]), "+f"(d[20]), "+f"(d[21]), "+f"(d[22]), "+f"(d[23]),
      "+f"(d[24]), "+f"(d[25]), "+f"(d[26]), "+f"(d[27]), "+f"(d[28]), "+f"(d[29]), "+f"(d[30]), "+f"(d[31]),
      "+f"(d[32]), "+f"(d[33]), "+f"(d[34]), "+f"(d[35]), "+f"(d[36]), "+f"(d[37]), "+f"(d[38]), "+f"(d[39]),
      "+f"(d[40]), "+f"(d[41]), "+f"(d[42]), "+f"(d[43]), "+f"(d[44]), "+f"(d[45]), "+f"(d[46]), "+f"(d[47]),
      "+f"(d[48]), "+f"(d[49]), "+f"(d[50]), "+f"(d[51]), "+f"(d[52]), "+f"(d[53]), "+f"(d[54]), "+f"(d[55])
    : "r"(a0), "r"(a1), "r"(a2), "r"(a3), "l"(descB), "r"(scaleD));
}

__device__ __forceinline__ void wgmma_rs_n128(float (&d)[64], uint32_t a0, uint32_t a1, uint32_t a2, uint32_t a3, uint64_t descB, int scaleD) {
  asm volatile(
    "{\n.reg .pred p;\nsetp.ne.b32 p, %69, 0;\n"
    "wgmma.mma_async.sync.aligned.m64n128k16.f32.bf16.bf16 "
    "{%0, %1, %2, %3, %4, %5, %6, %7, %8, %9, %10, %11, %12, %13, %14, %15, "
    "%16, %17, %18, %19, %20, %21, %22, %23, %24, %25, %26, %27, %28, %29, %30, %31, "
    "%32, %33, %34, %35, %36, %37, %38, %39, %40, %41, %42, %43, %44, %45, %46, %47, "
    "%48, %49, %50, %51, %52, %53, %54, %55, %56, %57, %58, %59, %60, %61, %62, %63}, "
    "{%64, %65, %66, %67}, %68, p, 1, 1, 1;\n}\n"
    : "+f"(d[0]), "+f"(d[1]), "+f"(d[2]), "+f"(d[3]), "+f"(d[4]), "+f"(d[5]), "+f"(d[6]), "+f"(d[7]),
      "+f"(d[8]), "+f"(d[9]), "+f"(d[10]), "+f"(d[11]), "+f"(d[12]), "+f"(d[13]), "+f"(d[14]), "+f"(d[15]),
      "+f"(d[16]), "+f"(d[17]), "+f"(d[18]), "+f"(d[19]), "+f"(d[20]), "+f"(d[21]), "+f"(d[22]), "+f"(d[23]),
      "+f"(d[24]), "+f"(d[25]), "+f"(d[26]), "+f"(d[27]), "+f"(d[28]), "+f"(d[29]), "+f"(d[30]), "+f"(d[31]),
      "+f"(d[32]), "+f"(d[33]), "+f"(d[34]), "+f"(d[35]), "+f"(d[36]), "+f"(d[37]), "+f"(d[38]), "+f"(d[39]),
      "+f"(d[40]), "+f"(d[41]), "+f"(d[42]), "+f"(d[43]), "+f"(d[44]), "+f"(d[45]), "+f"(d[46]), "+f"(d[47]),
      "+f"(d[48]), "+f"(d[49]), "+f"(d[50]), "+f"(d[51]), "+f"(d[52]), "+f"(d[53]), "+f"(d[54]), "+f"(d[55]),
      "+f"(d[56]), "+f"(d[57]), "+f"(d[58]), "+f"(d[59]), "+f"(d[60]), "+f"(d[61]), "+f"(d[62]), "+f"(d[63])
    : "r"(a0), "r"(a1), "r"(a2), "r"(a3), "l"(descB), "r"(scaleD));
}


__device__ __forceinline__ void mma16816(float (&c)[4], uint32_t a0, uint32_t a1, uint32_t a2, uint32_t a3, uint32_t b0, uint32_t b1) {
  asm("mma.sync.aligned.m16n8k16.row.col.f32.bf16.bf16.f32 {%0,%1,%2,%3}, {%4,%5,%6,%7}, {%8,%9}, {%0,%1,%2,%3};"
      : "+f"(c[0]), "+f"(c[1]), "+f"(c[2]), "+f"(c[3])
      : "r"(a0), "r"(a1), "r"(a2), "r"(a3), "r"(b0), "r"(b1));
}
__device__ __forceinline__ void stmatrix_x4(uint32_t addr, uint32_t r0, uint32_t r1, uint32_t r2, uint32_t r3) {
  asm volatile("stmatrix.sync.aligned.m8n8.x4.shared.b16 [%0], {%1,%2,%3,%4};" ::"r"(addr), "r"(r0), "r"(r1), "r"(r2), "r"(r3) : "memory");
}
__device__ __forceinline__ void ldmatrix_x4(uint32_t addr, uint32_t& r0, uint32_t& r1, uint32_t& r2, uint32_t& r3) {
  asm volatile("ldmatrix.sync.aligned.m8n8.x4.shared.b16 {%0,%1,%2,%3}, [%4];"
               : "=r"(r0), "=r"(r1), "=r"(r2), "=r"(r3)
               : "r"(addr)
               : "memory");
}
__device__ __forceinline__ void ldmatrix_x4_trans(uint32_t addr, uint32_t& r0, uint32_t& r1, uint32_t& r2, uint32_t& r3) {
  asm volatile("ldmatrix.sync.aligned.m8n8.x4.trans.shared.b16 {%0,%1,%2,%3}, [%4];"
               : "=r"(r0), "=r"(r1), "=r"(r2), "=r"(r3)
               : "r"(addr)
               : "memory");
}
__device__ __forceinline__ uint32_t pack_bf16(float lo, float hi) {
  uint32_t r;
  asm("cvt.rn.bf16x2.f32 %0, %1, %2;" : "=r"(r) : "f"(hi), "f"(lo));
  return r;
}
__device__ __forceinline__ float bf_lo(uint32_t v) { return __uint_as_float(v << 16); }
__device__ __forceinline__ float bf_hi(uint32_t v) { return __uint_as_float(v & 0xffff0000u); }
__device__ __forceinline__ float bf16r(float x) { return bf_lo(pack_bf16(x, 0.f)); }
__device__ __forceinline__ uint32_t hsub2_bf16(uint32_t a, uint32_t b) {
  uint32_t r;
  asm("sub.rn.bf16x2 %0, %1, %2;" : "=r"(r) : "r"(a), "r"(b));
  return r;
}
__device__ __forceinline__ uint32_t hadd2_bf16(uint32_t a, uint32_t b) {
  uint32_t r;
  asm("add.rn.bf16x2 %0, %1, %2;" : "=r"(r) : "r"(a), "r"(b));
  return r;
}
__device__ __forceinline__ uint32_t hmul2_bf16(uint32_t a, uint32_t b) {
  uint32_t r;
  asm("mul.rn.bf16x2 %0, %1, %2;" : "=r"(r) : "r"(a), "r"(b));
  return r;
}
__device__ __forceinline__ void ln_params(float mean, float var, uint32_t& m2, float& rinv) {
  m2 = pack_bf16(mean, mean);
  const float ve = bf16r(bf16r(var) + 1e-5f);
  rinv = 1.0f / bf16r(sqrtf(ve));
}
__device__ __forceinline__ float ex2_approx(float x) {
  float r;
  asm("ex2.approx.ftz.f32 %0, %1;" : "=f"(r) : "f"(x));
  return r;
}
__device__ __forceinline__ float rcp_approx(float x) {
  float r;
  asm("rcp.approx.ftz.f32 %0, %1;" : "=f"(r) : "f"(x));
  return r;
}
__device__ __forceinline__ uint32_t phi_pack(float a, float b) {
  const uint32_t t = pack_bf16(a, b);
  const uint32_t lin = hadd2_bf16(t, 0x3F803F80u);
  const uint32_t ex = pack_bf16(ex2_approx(bf_lo(t) * 1.4426950408889634f), ex2_approx(bf_hi(t) * 1.4426950408889634f));
  uint32_t mask;
  asm("set.gt.u32.bf16x2 %0, %1, %2;" : "=r"(mask) : "r"(t), "r"(0u));
  const uint32_t p = (lin & mask) | (ex & ~mask);
  return hadd2_bf16(p, 0x35863586u);
}
__device__ __forceinline__ uint4 ldg_nc(const uint4* p) {
  uint4 v;
  asm volatile("ld.global.nc.L1::no_allocate.v4.u32 {%0,%1,%2,%3}, [%4];" : "=r"(v.x), "=r"(v.y), "=r"(v.z), "=r"(v.w) : "l"(p));
  return v;
}
__device__ __forceinline__ uint4 ldg_cg(const uint4* p) {
  uint4 v;
  asm volatile("ld.global.cg.v4.u32 {%0,%1,%2,%3}, [%4];" : "=r"(v.x), "=r"(v.y), "=r"(v.z), "=r"(v.w) : "l"(p) : "memory");
  return v;
}
__device__ __forceinline__ uint4 ld_x(const uint4* p) {
  uint4 v;
  asm volatile("{\n.reg .b128 q;\nld.relaxed.gpu.global.b128 q, [%4];\nmov.b128 {%0,%1,%2,%3}, q;\n}\n"
               : "=r"(v.x), "=r"(v.y), "=r"(v.z), "=r"(v.w)
               : "l"(p)
               : "memory");
  return v;
}
__device__ __forceinline__ void st_x(uint4* p, uint32_t a, uint32_t b, uint32_t c, uint32_t d) {
  asm volatile("{\n.reg .b128 q;\nmov.b128 q, {%1,%2,%3,%4};\nst.relaxed.gpu.global.b128 [%0], q;\n}\n" ::"l"(p), "r"(a), "r"(b), "r"(c), "r"(d)
               : "memory");
}
__device__ __forceinline__ uint32_t ld_acquire(const uint32_t* p) {
  uint32_t v;
  asm volatile("ld.acquire.gpu.global.u32 %0, [%1];" : "=r"(v) : "l"(p) : "memory");
  return v;
}
__device__ __forceinline__ void red_add_v4(float4* p, float a, float b, float c, float d) {
  asm volatile("red.relaxed.gpu.global.add.v4.f32 [%0], {%1,%2,%3,%4};" ::"l"(p), "f"(a), "f"(b), "f"(c), "f"(d) : "memory");
}
__device__ __forceinline__ void named_bar(int id) { asm volatile("bar.sync %0, 128;" ::"r"(id) : "memory"); }

template <int N>
__device__ __forceinline__ void fetch(uint4* r, const uint4* p) {
#pragma unroll
  for (int i = 0; i < N; ++i) r[i] = ld_x(p + i * 32);
}
template <int N, uint32_t SENT = POISON>
__device__ __forceinline__ bool any_poison(const uint4* r) {
  bool bad = false;
#pragma unroll
  for (int i = 0; i < N; ++i) bad |= (r[i].x == SENT);
  return __any_sync(0xffffffffu, bad);
}
template <int N, uint32_t SENT = POISON>
__device__ __forceinline__ void ensure(uint4* r, const uint4* p) {
  if (__builtin_expect((any_poison<N, SENT>(r)), 0)) {
#pragma unroll 1
    for (int it = 0; it < SPIN_LIMIT; ++it) {
      fetch<N>(r, p);
      if (!any_poison<N, SENT>(r)) break;
    }
  }
}

template <uint32_t SENT>
__device__ __forceinline__ void poll_sources(const uint4* base, int frags_per_src, int nsrc_mask, int lane) {
  const uint32_t* p = reinterpret_cast<const uint32_t*>(base + (((lane & nsrc_mask) + 1) * frags_per_src - 1) * 32 + 31);
  uint32_t v0, v1;
  asm volatile("ld.relaxed.gpu.global.u32 %0, [%1];" : "=r"(v0) : "l"(p) : "memory");
#pragma unroll 1
  for (int it = 0; it < SPIN_LIMIT; ++it) {
    asm volatile("ld.relaxed.gpu.global.u32 %0, [%1];" : "=r"(v1) : "l"(p) : "memory");
    if (!__any_sync(0xffffffffu, v0 == SENT)) break;
    asm volatile("ld.relaxed.gpu.global.u32 %0, [%1];" : "=r"(v0) : "l"(p) : "memory");
    if (!__any_sync(0xffffffffu, v1 == SENT)) break;
  }
}

struct Params {
  const __nv_bfloat16* x;
  const __nv_bfloat16* w_gate;
  const __nv_bfloat16* w_up;
  __nv_bfloat16* out;
};

__global__ void __launch_bounds__(384, 1)
fused_block_kernel(const __grid_constant__ CUtensorMap tm_x, const __grid_constant__ CUtensorMap tm_qkv, const __grid_constant__ CUtensorMap tm_wo,
                   const __grid_constant__ CUtensorMap tm_down64, const __grid_constant__ CUtensorMap tm_down48, const Params prm) {
  extern __shared__ __align__(1024) uint8_t smem[];
  const uint32_t sbase = smem_u32(smem);
  const int tid = threadIdx.x;
  const int warp = tid >> 5, lane = tid & 31;
  const int b = blockIdx.x;
  const int cm = b & 1, cp = b >> 1;
  int dom, pos;
  if (cp < 4) { dom = 15; pos = cp; }
  else if (cp < 36) { dom = (cp - 4) & 7; pos = (cp - 4) >> 3; }
  else { dom = 8 + (cp - 36) % 7; pos = (cp - 36) / 7; }
  const int ti1 = cp >> 2, tj1 = 2 * (cp & 3) + cm;
  const int tiA = 2 * (dom >> 1) + cm, tjA = (dom & 1) * 4 + pos;
  const int rtB = 2 * dom + cm, jjB = pos;
  const uint32_t bar_full = sbase + SM_BAR, bar_empty = sbase + SM_BAR + NST * 8;
  const uint32_t bar_epoch = sbase + SM_EBAR, bar_kv = sbase + SM_KBAR, bar_pass = sbase + SM_PBAR, bar_pub = sbase + SM_UBAR;

  if (tid == 256) {
    asm volatile("prefetch.tensormap [%0];" ::"l"((uint64_t)&tm_x) : "memory");
    asm volatile("prefetch.tensormap [%0];" ::"l"((uint64_t)&tm_qkv) : "memory");
    asm volatile("prefetch.tensormap [%0];" ::"l"((uint64_t)&tm_wo) : "memory");
    asm volatile("prefetch.tensormap [%0];" ::"l"((uint64_t)&tm_down64) : "memory");
    asm volatile("prefetch.tensormap [%0];" ::"l"((uint64_t)&tm_down48) : "memory");
  }
  if (tid == 0) {
    for (int s = 0; s < NST; ++s) {
      mbar_init(bar_full + s * 8, 1);
      mbar_init(bar_empty + s * 8, 4);
    }
    mbar_init(bar_epoch, 1);
    mbar_init(bar_kv, 1);
    for (int p = 0; p < 6; ++p) mbar_init(bar_pass + p * 8, 1);
    for (int p = 0; p < 8; ++p) mbar_init(bar_pub + p * 8, 4);
    asm volatile("fence.mbarrier_init.release.cluster;" ::: "memory");
  }
  __syncthreads();
  asm volatile("barrier.cluster.arrive.relaxed.aligned;" ::: "memory");

  if (warp >= 8) {
    asm volatile("setmaxnreg.dec.sync.aligned.u32 40;");
    const int pw = warp - 8;
    if (pw == 2 && lane == 0) {
      uint32_t e;
      asm volatile("ld.relaxed.gpu.global.u32 %0, [%1];" : "=r"(e) : "l"(&g_epoch) : "memory");
      *reinterpret_cast<volatile uint32_t*>(smem + SM_MISC) = e;
      mbar_arrive(bar_epoch);
    }
    asm volatile("barrier.cluster.wait.aligned;" ::: "memory");
    if (pw < 2) {
      if (lane == 0) {
        bool gu_ready = false;
#pragma unroll 1
        for (int n = pw; n < NSTAGES; n += 2) {
          const int st = n % NST;
          const uint32_t fb = bar_full + st * 8, dst = sbase + st * STAGE_BYTES;
          if (n >= NST) mbar_wait(bar_empty + st * 8, ((n / NST) - 1) & 1);
          if (n == N_KV + pw) mbar_wait(bar_full + (N_X + 4 + pw) * 8, 0);
          const bool short_tile = n >= N_DN + 8;
          mbar_expect_tx(fb, short_tile ? 12288 : STAGE_BYTES);
          if (n >= N_KV && n < N_WO) {
            if (n < N_Q) {
              tma_3d(dst, &tm_qkv, fb, 64 * (n - N_KV), 8 + tj1);
              tma_3d(dst + 8192, &tm_qkv, fb, 64 * (n - N_KV), 16 + tj1);
            } else {
              tma_3d(dst, &tm_qkv, fb, 128 * (n - N_Q), tj1);
              tma_3d(dst + 8192, &tm_qkv, fb, 128 * (n - N_Q) + 64, tj1);
            }
            continue;
          }
          if (pw != cm) continue;
          if (n < N_KV) {
            tma_3d_mc(dst, &tm_x, fb, (2 * ti1 + (n & 1)) * 64, 2 * (n >> 1));
          } else if (n < N_GU) {
            const int r = n - N_WO;
            tma_3d_mc(dst, &tm_wo, fb, 64 * ((r >> 1) + 4 * (r & 1)), 2 * jjB);
          } else if (n < N_DN) {
            if (!gu_ready) {
              mbar_wait(bar_kv, 0);
              asm volatile("fence.proxy.async.global;" ::: "memory");
              gu_ready = true;
            }
            bulk_g2s_mc(dst, g_wgu + (size_t)(tjA * 24 + (n - N_GU)) * 1024, STAGE_BYTES, fb);
          } else {
            const int u = n - N_DN;
            if (short_tile) {
              tma_3d_mc(dst, &tm_down48, fb, 176 * (2 * (u - 8)) + 128, tjA);
              tma_3d_mc(dst + 8192, &tm_down48, fb, 176 * (2 * (u - 8) + 1) + 128, tjA);
            } else {
              tma_3d_mc(dst, &tm_down64, fb, 176 * (2 * (u & 3)) + 64 * (u >> 2), tjA);
              tma_3d_mc(dst + 8192, &tm_down64, fb, 176 * (2 * (u & 3) + 1) + 64 * (u >> 2), tjA);
            }
          }
        }
      }
      __syncwarp();
    } else {
      const int wg = pw - 2;
      mbar_wait(bar_epoch, 0);
      const uint32_t tag = *reinterpret_cast<volatile uint32_t*>(smem + SM_MISC) + 1;
      {
        const int tjB = 2 * jjB + wg;
#pragma unroll 1
        for (int w = 0; w < 4; ++w) {
          const int slab1 = (2 * ti1 + wg) * 4 + w, slabB = rtB * 4 + w;
#pragma unroll
          for (int q = 0; q < 4; ++q) {
            g_h[(slabB * 32 + 4 * tjB + q) * 32 + lane] = make_uint4(POISON, POISON, POISON, POISON);
            g_pq[tag & 1][(slab1 * 32 + 4 * tj1 + q) * 32 + lane] = make_uint4(0, 0, 0, 0);
          }
          if (lane < 16) reinterpret_cast<uint2*>(g_hstat)[(slabB * 16 + lane) * 8 + tjB] = make_uint2(POISON, POISON);
        }
      }
      asm volatile("bar.sync 9, 64;" ::: "memory");
      if (wg == 0) {
#pragma unroll 1
        for (int v = 0; v < 2; ++v) {
          mbar_wait(bar_pub + v * 8, 0);
          if (lane == 0) asm volatile("red.release.gpu.global.add.u32 [%0], 1;" ::"l"(&g_kvcnt[tj1 * 32]) : "memory");
        }
        const uint32_t target = 32u * tag;
#pragma unroll 1
        for (int it = 0; it < SPIN_LIMIT; ++it) {
          uint32_t v = target;
          if (lane < 8) v = ld_acquire(&g_kvcnt[lane * 32]);
          if (__all_sync(0xffffffffu, (int)(v - target) >= 0)) break;
        }
        __syncwarp();
        if (lane == 0) {
          const int par = (tag - 1) & 1;
          asm volatile("fence.proxy.async.global;" ::: "memory");
          mbar_expect_tx(bar_kv, 32768 + 2048);
          bulk_g2s_mc(sbase + SM_STAGE + cm * 16384, &g_kv[par][cm * 1024], 16384, bar_kv);
          bulk_g2s_mc(sbase + SM_ZF + cm * 1024, &g_z[par][cm * 64], 1024, bar_kv);
        }
#pragma unroll 1
        for (int pv = 0; pv < 6; ++pv) {
          const int p = pv >> 1, v = pv & 1;
          mbar_wait(bar_pub + (2 + pv) * 8, 0);
          if (lane == 0) asm volatile("st.release.gpu.global.u32 [%0], %1;" ::"l"(&g_hhflag[((2 * tiA + v) * 3 + p) * 8 + tjA]), "r"(tag) : "memory");
        }
      } else {
        mbar_wait(bar_kv, 0);
#pragma unroll 1
        for (int pv = 0; pv < 6; ++pv) {
          const uint32_t* f = &g_hhflag[((2 * tiA + (pv & 1)) * 3 + (pv >> 1)) * 8 + (lane & 7)];
#pragma unroll 1
          for (int it = 0; it < SPIN_LIMIT; ++it) {
            if (__all_sync(0xffffffffu, ld_acquire(f) == tag)) break;
            __nanosleep(100);
          }
          __syncwarp();
          if (lane == 0) mbar_arrive(bar_pass + pv * 8);
        }
      }
    }
  } else {
    asm volatile("setmaxnreg.inc.sync.aligned.u32 232;");
    const int wg = warp >> 2, w = warp & 3;
    const int g = lane >> 2, t = lane & 3;
    const int tw = tid & 127;
    const uint32_t stage = sbase + SM_STAGE + wg * 16384;
    const uint32_t dlo = ((sbase & 0x3FFFFu) >> 4) | ((8192u >> 4) << 16);
    const int slab1 = (2 * ti1 + wg) * 4 + w;
    const int slabA = (2 * tiA + wg) * 4 + w, rowA = slabA * 16 + g;
    const int slabB = rtB * 4 + w, rowB = slabB * 16 + g, tjB = 2 * jjB + wg;
    auto wait_stage = [&](int n) { mbar_wait(bar_full + (n % NST) * 8, (n / NST) & 1); };
    auto wg_wait1 = [&]() { wgmma_wait<1>(); };
    auto rel_stage = [&](int n, int weight) {
      if (tw < 2) mbar_arrive_cluster(bar_empty + (n % NST) * 8, tw, weight);
    };
    auto desc_at = [&](int n, int off) { return make_desc(dlo + (n % NST) * (STAGE_BYTES >> 4) + (off >> 4)); };
    auto order_wait = [&]() { asm volatile("bar.sync %0, 256;" ::"r"(7 + wg) : "memory"); };
    auto order_arrive = [&]() { asm volatile("bar.arrive %0, 256;" ::"r"(8 - wg) : "memory"); };
    if (wg == 1) order_arrive();
    auto publish = [&](int ev) { __syncwarp(); if (lane == 0) mbar_arrive(bar_pub + (2 * ev + wg) * 8); };

    uint32_t a[32][4];
    float r0, r1;
    {
      uint4 rp[6];
      {
        const __nv_bfloat16* src = ((b >> 6) ? prm.w_up : prm.w_gate) + (size_t)(64 * ((b >> 3) & 7)) * FF + 176 * (b & 7);
        const int nch = ((b & 7) == 7) ? 18 : 22;
#pragma unroll
        for (int u = 0; u < 6; ++u) {
          const int idx = u * 256 + tid;
          const int r = idx / 22, cc = idx - r * 22;
          rp[u] = make_uint4(0, 0, 0, 0);
          if (idx < 1408 && cc < nch) rp[u] = ldg_nc(reinterpret_cast<const uint4*>(src + (size_t)r * FF + cc * 8));
        }
      }
      asm volatile("barrier.cluster.wait.aligned;" ::: "memory");
      float s[2][4] = {}, q1[2][4] = {}, q2[2][4] = {};
      float f0 = 0.f, f1 = 0.f, f2 = 0.f, f3 = 0.f;
      constexpr uint32_t ONES = 0x3F803F80u;
#pragma unroll
      for (int c = 0; c < 4; ++c) {
        const int n = N_X + 2 * c + wg;
        wait_stage(n);
        const int xrow = w * 16 + ((lane >> 3) & 1) * 8 + (lane & 7);
        const uint32_t xs = sbase + (n % NST) * STAGE_BYTES + xrow * 128;
#pragma unroll
        for (int kk = 0; kk < 8; ++kk) {
          const int k = 8 * c + kk;
          ldmatrix_x4(xs + (kk >> 2) * 8192 + (((2 * (kk & 3) + (lane >> 4)) ^ (xrow & 7)) << 4), a[k][0], a[k][1], a[k][2], a[k][3]);
          mma16816(s[kk & 1], a[k][0], a[k][1], a[k][2], a[k][3], ONES, ONES);
          if (kk & 1) {
            f0 = fmaf(bf_lo(a[k][0]), bf_lo(a[k][0]), f0); f0 = fmaf(bf_hi(a[k][0]), bf_hi(a[k][0]), f0);
            f1 = fmaf(bf_lo(a[k][1]), bf_lo(a[k][1]), f1); f1 = fmaf(bf_hi(a[k][1]), bf_hi(a[k][1]), f1);
            f2 = fmaf(bf_lo(a[k][2]), bf_lo(a[k][2]), f2); f2 = fmaf(bf_hi(a[k][2]), bf_hi(a[k][2]), f2);
            f3 = fmaf(bf_lo(a[k][3]), bf_lo(a[k][3]), f3); f3 = fmaf(bf_hi(a[k][3]), bf_hi(a[k][3]), f3);
          } else {
            mma16816(q1[(kk >> 1) & 1], a[k][0], a[k][1], a[k][2], a[k][3], a[k][0], a[k][2]);
            mma16816(q2[(kk >> 1) & 1], a[k][0], a[k][1], a[k][2], a[k][3], a[k][1], a[k][3]);
          }
        }
        named_bar(1 + wg);
        rel_stage(n, 2);
      }
      const int srcl = g * 4 + (g >> 1);
      f0 += f2; f1 += f3;
      f0 += __shfl_xor_sync(0xffffffffu, f0, 1); f1 += __shfl_xor_sync(0xffffffffu, f1, 1);
      f0 += __shfl_xor_sync(0xffffffffu, f0, 2); f1 += __shfl_xor_sync(0xffffffffu, f1, 2);
      const float ssq0 = f0 + __shfl_sync(0xffffffffu, (g & 1) ? q1[0][1] + q1[1][1] : q1[0][0] + q1[1][0], srcl);
      const float ssq1 = f1 + __shfl_sync(0xffffffffu, (g & 1) ? q2[0][3] + q2[1][3] : q2[0][2] + q2[1][2], srcl);
      const float mean0 = (s[0][0] + s[1][0]) * (1.0f / DM), mean1 = (s[0][2] + s[1][2]) * (1.0f / DM);
      const float var0 = fmaxf(ssq0 * (1.0f / DM) - mean0 * mean0, 0.f);
      const float var1 = fmaxf(ssq1 * (1.0f / DM) - mean1 * mean1, 0.f);
      uint32_t m0, m1;
      ln_params(mean0, var0, m0, r0);
      ln_params(mean1, var1, m1, r1);
#pragma unroll
      for (int k = 0; k < 32; ++k) {
        a[k][0] = hsub2_bf16(a[k][0], m0);
        a[k][1] = hsub2_bf16(a[k][1], m1);
        a[k][2] = hsub2_bf16(a[k][2], m0);
        a[k][3] = hsub2_bf16(a[k][3], m1);
      }
      {
        uint4* dst = g_wgu + (size_t)(((b & 7) * 24 + ((b >> 3) & 7)) * 2 + (b >> 6)) * 512;
        const int nch = ((b & 7) == 7) ? 18 : 22;
#pragma unroll
        for (int u = 0; u < 6; ++u) {
          const int idx = u * 256 + tid;
          const int r = idx / 22, cc = idx - r * 22;
          if (idx < 1408 && cc < nch) dst[(cc >> 3) * 8 * 1024 + r * 8 + ((cc & 7) ^ (r & 7))] = rp[u];
        }
      }
    }
    mbar_wait(bar_epoch, 0);
    const uint32_t epoch = *reinterpret_cast<volatile uint32_t*>(smem + SM_MISC);
    const uint32_t tag = epoch + 1;
    const int par = epoch & 1;
    const uint4* hhsrc = g_hh + slabA * 88 * 32 + lane;
    auto load_group = [&](int slot, int n) {
      const int p = n >> 3;
      const uint4* s = hhsrc + (11 * (n & 7) + 4 * p) * 32;
#pragma unroll
      for (int ks = 0; ks < 4; ++ks) {
        if (ks < 3 || p < 2) {
          const uint4 v = ldg_cg(s + ks * 32);
          a[4 * slot + ks][0] = v.x; a[4 * slot + ks][1] = v.y; a[4 * slot + ks][2] = v.z; a[4 * slot + ks][3] = v.w;
        }
      }
    };
    auto wait_pass = [&](int p) { mbar_wait(bar_pass + (2 * p + wg) * 8, 0); };
    auto gemm_k512 = [&](float (&acc)[64], int n0, auto narrow, auto prep) {
      asm volatile("" : "+r"(n0));
      int st = n0 % NST, ph = (n0 / NST) & 1, prev = 0;
#pragma unroll
      for (int kt = 0; kt < 8; ++kt) {
        prep(kt);
        if ((kt & 3) == 0) order_wait();
        { mbar_wait(bar_full + st * 8, ph); }
        wgmma_fence();
        const uint32_t d0 = dlo + st * (STAGE_BYTES >> 4);
#pragma unroll
        for (int ks = 0; ks < 4; ++ks) {
          const int k = 4 * kt + ks;
          if constexpr (decltype(narrow)::value)
            wgmma_rs_n112(*reinterpret_cast<float (*)[56]>(&acc[0]), a[k][0], a[k][1], a[k][2], a[k][3], make_desc(d0 + ks * 128), k > 0);
          else
            wgmma_rs_n128(acc, a[k][0], a[k][1], a[k][2], a[k][3], make_desc(d0 + ks * 128), k > 0);
        }
        wgmma_commit();
        if ((kt & 3) == 3 && !(decltype(narrow)::value && kt == 7 && wg == 1)) order_arrive();
        if (kt > 0) {
          wg_wait1();
          if (tw < 2) mbar_arrive_cluster(bar_empty + prev * 8, tw, 1);
          if constexpr (decltype(narrow)::value) {
            if (kt == 1) wait_pass(0);
            load_group(kt - 1, kt - 1);
          }
        }
        prev = st;
        if (++st == NST) { st = 0; ph ^= 1; }
      }
      wgmma_wait<0>();
      if (tw < 2) mbar_arrive_cluster(bar_empty + prev * 8, tw, 1);
      if constexpr (decltype(narrow)::value) load_group(7, 7);
    };
    {
      float acc[64];
      gemm_k512(acc, N_KV, std::false_type{}, [](int) {});
      {
        const int mrow = w * 16 + ((lane >> 3) & 1) * 8 + (lane & 7);
        const int mch = lane >> 4;
#pragma unroll
        for (int hh = 0; hh < 4; ++hh) {
          const uint32_t off = mrow * 128 + (((2 * hh + mch) ^ (mrow & 7)) << 4);
          stmatrix_x4(stage + off, phi_pack(acc[8 * hh + 0] * r0, acc[8 * hh + 1] * r0), phi_pack(acc[8 * hh + 2] * r1, acc[8 * hh + 3] * r1),
                      phi_pack(acc[8 * hh + 4] * r0, acc[8 * hh + 5] * r0), phi_pack(acc[8 * hh + 6] * r1, acc[8 * hh + 7] * r1));
          stmatrix_x4(stage + 8192 + off, pack_bf16(acc[32 + 8 * hh + 0] * r0, acc[32 + 8 * hh + 1] * r0),
                      pack_bf16(acc[32 + 8 * hh + 2] * r1, acc[32 + 8 * hh + 3] * r1),
                      pack_bf16(acc[32 + 8 * hh + 4] * r0, acc[32 + 8 * hh + 5] * r0),
                      pack_bf16(acc[32 + 8 * hh + 6] * r1, acc[32 + 8 * hh + 7] * r1));
        }
      }
      named_bar(1 + wg);
    }
    {
      constexpr uint32_t ONES = 0x3F803F80u;
      float d0[4] = {}, d1[4] = {}, z0[4] = {}, z1[4] = {};
#pragma unroll
      for (int ks = 0; ks < 4; ++ks) {
        uint32_t va0, va1, va2, va3, pb0, pb1, pb2, pb3;
        {
          const int r = 16 * ks + (lane >> 4) * 8 + (lane & 7);
          const int ch = 2 * w + ((lane >> 3) & 1);
          ldmatrix_x4_trans(stage + 8192 + r * 128 + ((ch ^ (r & 7)) << 4), va0, va1, va2, va3);
        }
        {
          const int r = 16 * ks + ((lane >> 3) & 1) * 8 + (lane & 7);
          const int ch = 2 * w + (lane >> 4);
          ldmatrix_x4_trans(stage + r * 128 + ((ch ^ (r & 7)) << 4), pb0, pb1, pb2, pb3);
        }
        mma16816(d0, va0, va1, va2, va3, pb0, pb1);
        mma16816(d1, va0, va1, va2, va3, pb2, pb3);
        mma16816(z0, ONES, ONES, ONES, ONES, pb0, pb1);
        mma16816(z1, ONES, ONES, ONES, ONES, pb2, pb3);
      }
      const int head = 4 * tj1 + w;
      float4* kvp = &g_kv[par][head * 64 + lane];
      red_add_v4(kvp, d0[0], d0[1], d1[0], d1[1]);
      red_add_v4(kvp + 32, d0[2], d0[3], d1[2], d1[3]);
      if (g == 0) red_add_v4(&g_z[par][head * 4 + t], z0[0], z0[1], z1[0], z1[1]);
      asm volatile("fence.proxy.async.global;" ::: "memory");
      publish(0);
    }
    {
      {
        float accq[32];
        order_wait();
#pragma unroll
        for (int kt = 0; kt < 8; ++kt) {
          if ((kt & 1) == 0) wait_stage(N_Q + (kt >> 1));
          wgmma_fence();
#pragma unroll
          for (int ks = 0; ks < 4; ++ks) {
            const int k = 4 * kt + ks;
            wgmma_rs_n64(accq, a[k][0], a[k][1], a[k][2], a[k][3], desc_at(N_Q + (kt >> 1), (kt & 1) * 8192 + ks * 2048), k > 0);
          }
          wgmma_commit();
          if (kt == 7) order_arrive();
          if (kt > 0) {
            wg_wait1();
            if ((kt & 1) == 0) rel_stage(N_Q + (kt >> 1) - 1, 1);
          }
        }
        wgmma_wait<0>();
        rel_stage(N_Q + 3, 1);
#pragma unroll
        for (int hh = 0; hh < 4; ++hh)
          st_x(&g_pq[par][(slab1 * 32 + 4 * tj1 + hh) * 32 + lane], phi_pack(accq[8 * hh + 0] * r0, accq[8 * hh + 1] * r0),
               phi_pack(accq[8 * hh + 2] * r1, accq[8 * hh + 3] * r1), phi_pack(accq[8 * hh + 4] * r0, accq[8 * hh + 5] * r0),
               phi_pack(accq[8 * hh + 6] * r1, accq[8 * hh + 7] * r1));
      }
      if (b < 32) {
        g_kv[par ^ 1][b * 64 + (tid & 63)] = make_float4(0.f, 0.f, 0.f, 0.f);
        if (tid < 4) g_z[par ^ 1][b * 4 + tid] = make_float4(0.f, 0.f, 0.f, 0.f);
      }
    }

    auto cross_reduce = [&](float (&acc)[64], float (&out)[32]) {
      float4* mine = reinterpret_cast<float4*>(smem + SM_STAGE + wg * 16384) + tw;
      const float4* theirs = reinterpret_cast<const float4*>(smem + SM_STAGE + (wg ^ 1) * 16384) + tw;
#pragma unroll
      for (int i = 0; i < 8; ++i)
        mine[i * 128] = wg ? make_float4(acc[4 * i], acc[4 * i + 1], acc[4 * i + 2], acc[4 * i + 3])
                           : make_float4(acc[32 + 4 * i], acc[32 + 4 * i + 1], acc[32 + 4 * i + 2], acc[32 + 4 * i + 3]);
      asm volatile("bar.sync 4, 256;" ::: "memory");
#pragma unroll
      for (int i = 0; i < 8; ++i) {
        const float4 v = theirs[i * 128];
        out[4 * i + 0] = (wg ? acc[32 + 4 * i + 0] : acc[4 * i + 0]) + v.x;
        out[4 * i + 1] = (wg ? acc[32 + 4 * i + 1] : acc[4 * i + 1]) + v.y;
        out[4 * i + 2] = (wg ? acc[32 + 4 * i + 2] : acc[4 * i + 2]) + v.z;
        out[4 * i + 3] = (wg ? acc[32 + 4 * i + 3] : acc[4 * i + 3]) + v.w;
      }
    };

    {
      uint32_t xr[4][4];
#pragma unroll
      for (int q = 0; q < 4; ++q) {
        const uint32_t* p0 = reinterpret_cast<const uint32_t*>(prm.x + (size_t)rowB * DM + 64 * tjB + 16 * q + 2 * t);
        xr[q][0] = __ldg(p0);
        xr[q][1] = __ldg(p0 + 8 * DM / 2);
        xr[q][2] = __ldg(p0 + 4);
        xr[q][3] = __ldg(p0 + 8 * DM / 2 + 4);
      }
      const uint4* osrc = &g_pq[par][(slabB * 32 + 16 * wg) * 32];
      uint4 of[16];
      poll_sources<0u>(osrc, 4, 3, lane);
      fetch<16>(of, osrc + lane);
      mbar_wait(bar_kv, 0);
      if (b == 0 && tid == 0) asm volatile("st.relaxed.gpu.global.u32 [%0], %1;" ::"l"(&g_epoch), "r"(tag) : "memory");
      float acc[64];
#pragma unroll
      for (int n = 0; n < 4; ++n) {
        const int sn = N_WO + 2 * n + wg;
        { ensure<4, 0u>(&of[4 * n], osrc + lane + 4 * n * 32); }
#pragma unroll
        for (int ks = 0; ks < 4; ++ks) {
          const int hl = 4 * n + ks;
          const float4 lo = *reinterpret_cast<const float4*>(smem + SM_STAGE + wg * 16384 + (hl * 64 + lane) * 16);
          const float4 hi = *reinterpret_cast<const float4*>(smem + SM_STAGE + wg * 16384 + (hl * 64 + 32 + lane) * 16);
          const float4 zz = *reinterpret_cast<const float4*>(smem + SM_ZF + ((16 * wg + hl) * 4 + t) * 16);
          uint4& p = of[hl];
          float n0[4] = {}, n1[4] = {}, dn[4] = {};
          mma16816(dn, p.x, p.y, p.z, p.w, pack_bf16(zz.x, zz.y), pack_bf16(zz.z, zz.w));
          mma16816(n0, p.x, p.y, p.z, p.w, pack_bf16(lo.x, lo.y), pack_bf16(lo.z, lo.w));
          mma16816(n1, p.x, p.y, p.z, p.w, pack_bf16(hi.x, hi.y), pack_bf16(hi.z, hi.w));
          const float i0 = rcp_approx(dn[0] + 1e-6f), i1 = rcp_approx(dn[2] + 1e-6f);
          p = make_uint4(pack_bf16(n0[0] * i0, n0[1] * i0), pack_bf16(n0[2] * i1, n0[3] * i1), pack_bf16(n1[0] * i0, n1[1] * i0),
                         pack_bf16(n1[2] * i1, n1[3] * i1));
        }
        wait_stage(sn);
        wgmma_fence();
#pragma unroll
        for (int ks = 0; ks < 4; ++ks)
          wgmma_rs_n128(acc, of[4 * n + ks].x, of[4 * n + ks].y, of[4 * n + ks].z, of[4 * n + ks].w, desc_at(sn, ks * 2048), (n | ks) > 0);
        wgmma_commit();
        if (n > 0) {
          wg_wait1();
          rel_stage(sn - 2, 2);
        }
      }
      wgmma_wait<0>();
      rel_stage(N_WO + 6 + wg, 2);
      named_bar(1 + wg);
      float sum[32];
      cross_reduce(acc, sum);

      uint32_t hf[4][4];
      float s0 = 0.f, s1 = 0.f;
#pragma unroll
      for (int q = 0; q < 4; ++q) {
#pragma unroll
        for (int r = 0; r < 4; ++r) {
          hf[q][r] = hadd2_bf16(xr[q][r], pack_bf16(sum[8 * q + 2 * r], sum[8 * q + 2 * r + 1]));
          const float sv = bf_lo(hf[q][r]) + bf_hi(hf[q][r]);
          if (r & 1) s1 += sv; else s0 += sv;
        }
        st_x(g_h + (slabB * 32 + 4 * tjB + q) * 32 + lane, hf[q][0], hf[q][1], hf[q][2], hf[q][3]);
      }
      s0 += __shfl_xor_sync(0xffffffffu, s0, 1); s1 += __shfl_xor_sync(0xffffffffu, s1, 1);
      s0 += __shfl_xor_sync(0xffffffffu, s0, 2); s1 += __shfl_xor_sync(0xffffffffu, s1, 2);
      const float mu0 = s0 * (1.0f / 64), mu1 = s1 * (1.0f / 64);
      float e0 = 0.f, e1 = 0.f;
#pragma unroll
      for (int q = 0; q < 4; ++q) {
#pragma unroll
        for (int r = 0; r < 4; ++r) {
          const float mu = (r & 1) ? mu1 : mu0;
          const float dl = bf_lo(hf[q][r]) - mu, dh = bf_hi(hf[q][r]) - mu;
          const float sv = dl * dl + dh * dh;
          if (r & 1) e1 += sv; else e0 += sv;
        }
      }
      e0 += __shfl_xor_sync(0xffffffffu, e0, 1); e1 += __shfl_xor_sync(0xffffffffu, e1, 1);
      e0 += __shfl_xor_sync(0xffffffffu, e0, 2); e1 += __shfl_xor_sync(0xffffffffu, e1, 2);
      if (t < 2) {
        const uint64_t pk = t == 0 ? ((uint64_t)__float_as_uint(e0) << 32 | __float_as_uint(mu0)) : ((uint64_t)__float_as_uint(e1) << 32 | __float_as_uint(mu1));
        const uint64_t* dst = reinterpret_cast<const uint64_t*>(g_hstat) + (rowB + 8 * t) * 8 + tjB;
        asm volatile("st.relaxed.gpu.global.u64 [%0], %1;" ::"l"(dst), "l"(pk) : "memory");
      }
    }

    {
      const uint4* hsrc = g_h + slabA * 32 * 32;
      uint32_t m0, m1;
      {
#pragma unroll 1
        for (int it = 0; it < SPIN_LIMIT; ++it) {
          const uint4 q = ld_x(&g_hstat[slabA * 64 + t]);
          if (!__any_sync(0xffffffffu, q.x == POISON || q.z == POISON)) break;
        }
        uint4 p0 = ld_x(&g_hstat[rowA * 4 + t]), p1 = ld_x(&g_hstat[(rowA + 8) * 4 + t]);
#pragma unroll
        for (int k = 0; k < 32; ++k) {
          const uint4 v = ld_x(hsrc + lane + k * 32);
          a[k][0] = v.x; a[k][1] = v.y; a[k][2] = v.z; a[k][3] = v.w;
        }
#pragma unroll 1
        for (int it = 0; it < SPIN_LIMIT; ++it) {
          if (!__any_sync(0xffffffffu, p0.x == POISON || p0.z == POISON || p1.x == POISON || p1.z == POISON)) break;
          p0 = ld_x(&g_hstat[rowA * 4 + t]);
          p1 = ld_x(&g_hstat[(rowA + 8) * 4 + t]);
        }
        const float a0x = __uint_as_float(p0.x), a0y = __uint_as_float(p0.y), a0z = __uint_as_float(p0.z), a0w = __uint_as_float(p0.w);
        const float a1x = __uint_as_float(p1.x), a1y = __uint_as_float(p1.y), a1z = __uint_as_float(p1.z), a1w = __uint_as_float(p1.w);
        float a0 = a0x + a0z, a1 = a1x + a1z;
        a0 += __shfl_xor_sync(0xffffffffu, a0, 1); a1 += __shfl_xor_sync(0xffffffffu, a1, 1);
        a0 += __shfl_xor_sync(0xffffffffu, a0, 2); a1 += __shfl_xor_sync(0xffffffffu, a1, 2);
        const float mean0 = a0 * 0.125f, mean1 = a1 * 0.125f;
        float v0 = a0y + a0w + 64.f * ((a0x - mean0) * (a0x - mean0) + (a0z - mean0) * (a0z - mean0));
        float v1 = a1y + a1w + 64.f * ((a1x - mean1) * (a1x - mean1) + (a1z - mean1) * (a1z - mean1));
        v0 += __shfl_xor_sync(0xffffffffu, v0, 1); v1 += __shfl_xor_sync(0xffffffffu, v1, 1);
        v0 += __shfl_xor_sync(0xffffffffu, v0, 2); v1 += __shfl_xor_sync(0xffffffffu, v1, 2);
        ln_params(mean0, v0 * (1.0f / DM), m0, r0);
        ln_params(mean1, v1 * (1.0f / DM), m1, r1);
      }
      auto prep_h = [&](int kt) {
        if (__builtin_expect(__any_sync(0xffffffffu, a[4 * kt][0] == POISON || a[4 * kt + 1][0] == POISON || a[4 * kt + 2][0] == POISON || a[4 * kt + 3][0] == POISON), 0)) {
#pragma unroll 1
          for (int it = 0; it < SPIN_LIMIT; ++it) {
            uint4 v[4];
            fetch<4>(v, hsrc + lane + 4 * kt * 32);
#pragma unroll
            for (int ks = 0; ks < 4; ++ks) { a[4 * kt + ks][0] = v[ks].x; a[4 * kt + ks][1] = v[ks].y; a[4 * kt + ks][2] = v[ks].z; a[4 * kt + ks][3] = v[ks].w; }
            if (!any_poison<4>(v)) break;
          }
        }

#pragma unroll
        for (int ks = 0; ks < 4; ++ks) {
          a[4 * kt + ks][0] = hsub2_bf16(a[4 * kt + ks][0], m0);
          a[4 * kt + ks][1] = hsub2_bf16(a[4 * kt + ks][1], m1);
          a[4 * kt + ks][2] = hsub2_bf16(a[4 * kt + ks][2], m0);
          a[4 * kt + ks][3] = hsub2_bf16(a[4 * kt + ks][3], m1);
        }
      };
#pragma unroll 1
      for (int p = 0; p < 3; ++p) {
        float acc[64];
        if (p == 0) gemm_k512(acc, N_GU + 8 * p, std::false_type{}, prep_h);
        else if (p == 1) gemm_k512(acc, N_GU + 8 * p, std::false_type{}, [](int) {});
        else gemm_k512(acc, N_GU + 8 * p, std::true_type{}, [](int) {});
#pragma unroll
        for (int qq = 0; qq < 4; ++qq) {
          if (qq < 3 || p < 2) {
            uint32_t v[4];
#pragma unroll
            for (int r = 0; r < 4; ++r) {
              const float sc = (r & 1) ? r1 : r0;
              v[r] = hmul2_bf16(pack_bf16(acc[8 * qq + 2 * r] * sc, acc[8 * qq + 2 * r + 1] * sc),
                                pack_bf16(acc[32 + 8 * qq + 2 * r] * sc, acc[32 + 8 * qq + 2 * r + 1] * sc));
            }
            g_hh[(slabA * 88 + 11 * tjA + 4 * p + qq) * 32 + lane] = make_uint4(v[0], v[1], v[2], v[3]);
          }
        }
        publish(1 + p);
      }
    }

    {
      float sum[32];
      uint32_t dl4 = dlo;
      asm volatile("" : "+r"(dl4));
#pragma unroll
      for (int n = 0; n < 24; ++n) {
        const int sn = N_DN + (n >> 1), sl = n & 7;
        if ((n & 1) == 0) wait_stage(sn);
        wgmma_fence();
#pragma unroll
        for (int ks = 0; ks < 4; ++ks)
          if (ks < 3 || n < 16)
            wgmma_rs_n64(sum, a[4 * sl + ks][0], a[4 * sl + ks][1], a[4 * sl + ks][2], a[4 * sl + ks][3], make_desc(dl4 + (sn % NST) * (STAGE_BYTES >> 4) + (((n & 1) * 8192 + ks * 2048) >> 4)), (n | ks) > 0);
        wgmma_commit();
        if (n > 0) {
          wg_wait1();
          if (n == 1) wait_pass(1);
          if (n == 9) wait_pass(2);
          if (n - 1 + 8 < 24) load_group((n - 1) & 7, n - 1 + 8);
        }
      }
      uint4 hf[4];
#pragma unroll
      for (int q = 0; q < 4; ++q) hf[q] = ldg_cg(&g_h[(slabA * 32 + 4 * tjA + q) * 32 + lane]);
      wgmma_wait<0>();
      const uint32_t wst = stage + w * 2048;
      {
        const int mrow = ((lane >> 3) & 1) * 8 + (lane & 7);
        const int mch = lane >> 4;
#pragma unroll
        for (int q = 0; q < 4; ++q) {
          stmatrix_x4(wst + mrow * 128 + (((2 * q + mch) ^ (mrow & 7)) << 4),
                      hadd2_bf16(hf[q].x, pack_bf16(sum[8 * q + 0], sum[8 * q + 1])), hadd2_bf16(hf[q].y, pack_bf16(sum[8 * q + 2], sum[8 * q + 3])),
                      hadd2_bf16(hf[q].z, pack_bf16(sum[8 * q + 4], sum[8 * q + 5])), hadd2_bf16(hf[q].w, pack_bf16(sum[8 * q + 6], sum[8 * q + 7])));
        }
      }
      __syncwarp();
#pragma unroll
      for (int it = 0; it < 4; ++it) {
        const int r = it * 4 + (lane >> 3), ch = lane & 7;
        uint4 v;
        asm volatile("ld.shared.v4.u32 {%0,%1,%2,%3}, [%4];" : "=r"(v.x), "=r"(v.y), "=r"(v.z), "=r"(v.w) : "r"(wst + r * 128 + ((ch ^ (r & 7)) << 4)));
        *reinterpret_cast<uint4*>(prm.out + (size_t)(slabA * 16 + r) * DM + 64 * tjA + ch * 8) = v;
      }
    }
  }
  asm volatile("barrier.cluster.arrive.relaxed.aligned;\nbarrier.cluster.wait.aligned;" ::: "memory");
}

typedef CUresult (*EncodeTiledFn)(CUtensorMap*, CUtensorMapDataType, cuuint32_t, void*, const cuuint64_t*, const cuuint64_t*,
                                  const cuuint32_t*, const cuuint32_t*, CUtensorMapInterleave, CUtensorMapSwizzle,
                                  CUtensorMapL2promotion, CUtensorMapFloatOOBfill);

void encode_blk(EncodeTiledFn enc, CUtensorMap* tm, const void* p, int rows, int cols, int box_rows, int box_blks) {
  cuuint64_t gd[3] = {64, (cuuint64_t)rows, (cuuint64_t)cols / 64};
  cuuint64_t gs[2] = {(cuuint64_t)cols * 2, 128};
  cuuint32_t bx[3] = {64, (cuuint32_t)box_rows, (cuuint32_t)box_blks};
  cuuint32_t es[3] = {1, 1, 1};
  enc(tm, CU_TENSOR_MAP_DATA_TYPE_BFLOAT16, 3, const_cast<void*>(p), gd, gs, bx, es, CU_TENSOR_MAP_INTERLEAVE_NONE,
      CU_TENSOR_MAP_SWIZZLE_128B, CU_TENSOR_MAP_L2_PROMOTION_L2_128B, CU_TENSOR_MAP_FLOAT_OOB_FILL_NONE);
}

}

extern "C" void kernel_launch(void* const* d_in, const int* in_sizes, int n_in, void* d_out, int out_size) {
  (void)in_sizes; (void)n_in; (void)out_size;
  static CUtensorMap tm_x, tm_qkv, tm_wo, tm_down64, tm_down48;
  static const void* cached[4] = {nullptr, nullptr, nullptr, nullptr};
  static bool attr_done = false;
  const void* ptrs[4] = {d_in[1], d_in[2], d_in[6], d_in[0]};
  bool same = true;
  for (int i = 0; i < 4; ++i) same = same && (cached[i] == ptrs[i]);
  if (!same) {
    void* fn = nullptr;
    cudaDriverEntryPointQueryResult qr;
    cudaGetDriverEntryPoint("cuTensorMapEncodeTiled", &fn, cudaEnableDefault, &qr);
    EncodeTiledFn enc = (EncodeTiledFn)fn;
    encode_blk(enc, &tm_qkv, ptrs[0], DM, 3 * DM, 64, 1);
    encode_blk(enc, &tm_wo, ptrs[1], DM, DM, 64, 2);
    encode_blk(enc, &tm_down64, ptrs[2], FF, DM, 64, 1);
    encode_blk(enc, &tm_down48, ptrs[2], FF, DM, 48, 1);
    encode_blk(enc, &tm_x, ptrs[3], 2048, DM, 64, 2);
    for (int i = 0; i < 4; ++i) cached[i] = ptrs[i];
  }
  if (!attr_done) {
    cudaFuncSetAttribute(fused_block_kernel, cudaFuncAttributeMaxDynamicSharedMemorySize, SM_TOTAL);
    attr_done = true;
  }
  Params prm;
  prm.x = (const __nv_bfloat16*)d_in[0];
  prm.w_gate = (const __nv_bfloat16*)d_in[4];
  prm.w_up = (const __nv_bfloat16*)d_in[5];
  prm.out = (__nv_bfloat16*)d_out;
  cudaLaunchConfig_t cfg = {};
  cfg.gridDim = dim3(NCTA);
  cfg.blockDim = dim3(384);
  cfg.dynamicSmemBytes = SM_TOTAL;
  cfg.stream = cudaStreamPerThread;
  cudaLaunchAttribute at[1];
  at[0].id = cudaLaunchAttributeClusterDimension;
  at[0].val.clusterDim.x = 2;
  at[0].val.clusterDim.y = 1;
  at[0].val.clusterDim.z = 1;
  cfg.attrs = at;
  cfg.numAttrs = 1;
  cudaLaunchKernelEx(&cfg, fused_block_kernel, tm_x, tm_qkv, tm_wo, tm_down64, tm_down48, prm);
}
```
